```python
import torch

def _softmax(x, axis=-1):
    return torch.softmax(x, dim=axis)
def _gelu(x):
    return torch.nn.functional.gelu(x, approximate="tanh")
def _silu(x):
    return torch.nn.functional.silu(x)
def _sigmoid(x):
    return torch.sigmoid(x)
def _layernorm(x, axis=-1, eps=1e-5):
    m = x.mean(dim=axis, keepdim=True)
    v = x.var(dim=axis, keepdim=True, unbiased=False)
    return (x - m) / torch.sqrt(v + eps)
def _scatter_add(tgt, idx, src, axis=0):
    return tgt.clone().index_add_(axis, idx, src)
def _segment_sum(src, seg, n):
    out = torch.zeros((n,) + src.shape[1:], dtype=src.dtype)
    return out.index_add_(0, seg, src)
def _pad(x, pw):
    flat = tuple(v for pair in reversed(pw) for v in pair)
    return torch.nn.functional.pad(x, flat)

kernel_name = 'standalone__detection_seg_dino__vision'

def setup_inputs():

    _w = (lambda a: (lambda t: t.to(torch.bfloat16) if t.is_floating_point() else t)(torch.as_tensor(a)))
    H = W = (512 // 2) * 2
    C = 192
    Nq = 16
    sc = C ** -0.5
    return {
        "q": _w((lambda *s: torch.randn(*s, dtype=torch.bfloat16) * 0.2)(1, Nq, C)),
        "f0": _w((lambda *s: torch.randn(*s, dtype=torch.bfloat16) * 3.2)(1, H, W, C)),
        "f1": _w((lambda *s: torch.randn(*s, dtype=torch.bfloat16) * 3.2)(1, H // 2, W // 2, C)),
        "wq": _w((lambda *s: torch.randn(*s, dtype=torch.bfloat16) * 1.6)(C, C) * sc),
        "wk": _w((lambda *s: torch.randn(*s, dtype=torch.bfloat16) * 1.6)(C, C) * sc),
        "wv": _w((lambda *s: torch.randn(*s, dtype=torch.bfloat16) * 3.2)(C, C) * sc),
        "wo": _w((lambda *s: torch.randn(*s, dtype=torch.bfloat16) * 3.2)(C, C) * sc),
    }

def reference(q, f0, f1, wq, wk, wv, wo):
    B, H, W, C = f0.shape
    f1u = (lambda x, n, axis: torch.repeat_interleave(x, n, dim=axis))((lambda x, n, axis: torch.repeat_interleave(x, n, dim=axis))(f1, 2, axis=1), 2, axis=2)
    fused = f0 + f1u
    feats = _layernorm(fused.reshape(B, H * W, C), axis=-1)
    qn = _layernorm(q, axis=-1)
    Q = torch.einsum("bnc,cd->bnd", qn, wq)
    K = torch.einsum("bmc,cd->bmd", feats, wk)
    V = torch.einsum("bmc,cd->bmd", feats, wv)
    scale = C ** -0.5
    logits = torch.einsum("bnd,bmd->bnm", Q, K) * scale
    attn = _softmax(logits, axis=-1)
    ctx = torch.einsum("bnm,bmd->bnd", attn, V)
    return q + torch.einsum("bnd,dc->bnc", ctx, wo)
```

```cpp
#include <cuda_runtime.h>
#include <cuda.h>
#include <cuda_bf16.h>
#include <stdint.h>

namespace {

constexpr int CH = 192;
constexpr int NTILES = 4096;
constexpr int STAGES = 7;
constexpr int STAGE_BYTES = 30720;
constexpr int NSERV = 12;
constexpr int CL = 8;
constexpr int MAXS = 128;
constexpr float LN_EPS = 1e-5f;
constexpr float EPS2 = LN_EPS * CH * CH;
constexpr float RESCALE_TH = 60.0f;
#define NSTATIC 6
#define JOIN_N 3
static_assert(NSTATIC >= JOIN_N + 3, "a service CTA starts with two static tiles and requests its first ticket with the third one");
#define ORDER_AT 6
#define CHECKPOINT 10
#define WSTAG 15
#define WT_AT (CHECKPOINT + WSTAG + 4)
#define PAUSE 12
#define D_END 1160
#define END_X 240
#define MID_D 675
#define MID_FROM 16
#define QK_AFTER 3
#define MEMNS 164
#define LLAG 1000
#define REL_Z 18
template <int N> __device__ __forceinline__ void pad() { if constexpr (N > 0) { asm volatile("pmevent 1;"); pad<N - 1>(); } }
constexpr unsigned SPIN_LIMIT = 1u << 22;
constexpr uint64_t EVICT_FIRST = 0x12F0000000000000ull;

constexpr uint32_t K_SB = 1024;
constexpr uint32_t K_SM_P = K_SB + STAGES * STAGE_BYTES;
constexpr uint32_t K_SM_A = K_SM_P + 4096;
constexpr uint32_t K_SM_XA = K_SB + (STAGES - 1) * STAGE_BYTES;
constexpr uint32_t K_SM_MX = K_SM_A + 6656;
constexpr uint32_t K_SM_UL = K_SM_MX + 256;
constexpr uint32_t K_SM_AL = K_SM_UL + 512;
constexpr uint32_t K_SM_FIN = K_SM_AL + 128;
constexpr uint32_t K_SM_FW = K_SM_FIN + 64;
constexpr uint32_t K_SM_FX = K_SM_FW + 768;
constexpr uint32_t K_SM_ZERO = K_SM_FX + 2048;
constexpr uint32_t K_SM_EP = K_SM_ZERO + 256;
constexpr uint32_t K_SM_FLAG = K_SM_EP + 16;
constexpr uint32_t K_BAR_FULL = K_SM_FLAG + 16, K_BAR_EMPTY = K_BAR_FULL + 8 * STAGES, K_BAR_W = K_BAR_EMPTY + 8 * STAGES;
constexpr uint32_t K_BAR_EP = K_BAR_W + 8;
constexpr uint32_t K_BAR_WT = K_BAR_EP + 8;
constexpr uint32_t K_BAR_V = K_BAR_WT + 8;
constexpr uint32_t K_BAR_JOB = K_BAR_V + 8;
constexpr uint32_t K_SM_INFO = K_BAR_JOB + 8 * 5;
constexpr uint32_t K_SM_TS = K_SM_INFO + 4 * STAGES + 4;
constexpr int SM_TOTAL = K_SM_TS - K_SB;
constexpr uint32_t K_SM_WQ = K_SB, K_SM_WK = K_SM_WQ + CH * CH * 2, K_SM_Q = K_SM_WK + 16 * CH * 2, K_SM_RED = K_SM_Q + 16 * CH * 2;
constexpr uint32_t K_SM_WV = K_SM_RED + 12288, K_SM_WO = K_SM_WV + CH * CH * 2;

#define SB (cb + K_SB)
#define SM_P (cb + K_SM_P)
#define SM_A (cb + K_SM_A)
#define SM_XA (cb + K_SM_XA)
#define SM_MX (cb + K_SM_MX)
#define SM_UL (cb + K_SM_UL)
#define SM_AL (cb + K_SM_AL)
#define SM_FIN (cb + K_SM_FIN)
#define SM_FW (cb + K_SM_FW)
#define SM_FX (cb + K_SM_FX)
#define SM_ZERO (cb + K_SM_ZERO)
#define SM_EP (cb + K_SM_EP)
#define SM_FLAG (cb + K_SM_FLAG)
#define BAR_FULL (cb + K_BAR_FULL)
#define BAR_EMPTY (cb + K_BAR_EMPTY)
#define BAR_W (cb + K_BAR_W)
#define BAR_EP (cb + K_BAR_EP)
#define BAR_WT (cb + K_BAR_WT)
#define BAR_V (cb + K_BAR_V)
#define BAR_JOB (cb + K_BAR_JOB)
#define SM_INFO (cb + K_SM_INFO)
#define SM_TS (cb + K_SM_TS)
#define SM_WQ (cb + K_SM_WQ)
#define SM_WK (cb + K_SM_WK)
#define SM_Q (cb + K_SM_Q)
#define SM_RED (cb + K_SM_RED)
#define SM_WV (cb + K_SM_WV)
#define SM_WO (cb + K_SM_WO)

struct __align__(128) Scratch {
    unsigned epoch, ctr, pad[30];
    unsigned flagW[128];
    uint4 qk[12 * 32];
    uint32_t wvo[3 * 4 * 12 * 128];
    uint4 M[8 * 128 * 2];
    uint4 L[8 * 128 * 2];
    uint4 T[8 * 128 * 2];
};
__device__ Scratch g_s;

__device__ __forceinline__ void spin_guard(unsigned it) {
    asm volatile("{\n.reg .pred p;\n.reg .b64 z;\nsetp.gt.u32 p, %0, %1;\nmov.b64 z, 0;\n@p st.global.u32 [z], %0;\n}" ::"r"(it), "n"(SPIN_LIMIT));
}
__device__ __forceinline__ uint32_t smem_u32(const void* p) { return (uint32_t)__cvta_generic_to_shared(p); }
__device__ __forceinline__ void mbar_init(uint32_t bar, int cnt) { asm volatile("mbarrier.init.shared::cta.b64 [%0], %1;" ::"r"(bar), "r"(cnt) : "memory"); }
__device__ __forceinline__ void mbar_expect_tx(uint32_t bar, uint32_t bytes) { asm volatile("mbarrier.arrive.expect_tx.shared::cta.b64 _, [%0], %1;" ::"r"(bar), "r"(bytes) : "memory"); }
__device__ __forceinline__ void mbar_arrive_if(uint32_t bar, uint32_t cond) {
    asm volatile("{\n.reg .pred p;\nsetp.ne.u32 p, %1, 0;\n@p mbarrier.arrive.shared::cta.b64 _, [%0];\n}" ::"r"(bar), "r"(cond) : "memory");
}
__device__ __forceinline__ void mbar_wait(uint32_t bar, uint32_t parity) {
    asm volatile("{\n.reg .pred p;\n.reg .u32 c;\n.reg .b64 z;\nmov.u32 c, 0;\nmov.b64 z, 0;\nbra.uni T_%=;\n"
                 "W_%=:\nadd.u32 c, c, 1;\nsetp.gt.u32 p, c, %2;\n@p st.global.u32 [z], c;\n"
                 "T_%=:\nmbarrier.try_wait.parity.shared::cta.b64 p, [%0], %1;\n@!p bra W_%=;\n}"
                 ::"r"(bar), "r"(parity), "n"(SPIN_LIMIT / 4) : "memory");
}
__device__ __forceinline__ void mbar_wait_u(uint32_t bar, uint32_t parity) {
    asm volatile("{\n.reg .pred p;\n.reg .u32 c;\n.reg .b64 z;\nmov.u32 c, 0;\nmov.b64 z, 0;\nbra.uni T_%=;\n"
                 "W_%=:\nadd.u32 c, c, 1;\nsetp.gt.u32 p, c, %2;\n@p st.global.u32 [z], c;\n"
                 "T_%=:\nmbarrier.try_wait.parity.shared::cta.b64 p, [%0], %1;\n@!p bra.uni W_%=;\n}"
                 ::"r"(bar), "r"(parity), "n"(SPIN_LIMIT / 4) : "memory");
}
__device__ __forceinline__ bool mbar_test(uint32_t bar, uint32_t parity) {
    uint32_t ok;
    asm volatile("{\n.reg .pred p;\nmbarrier.test_wait.parity.shared::cta.b64 p, [%1], %2;\nselp.u32 %0, 1, 0, p;\n}" : "=r"(ok) : "r"(bar), "r"(parity) : "memory");
    return ok != 0;
}
__device__ __forceinline__ void tma3d(uint32_t dst, const CUtensorMap* tm, int c0, int c1, int c2, uint32_t bar) {
    asm volatile("cp.async.bulk.tensor.3d.shared::cluster.global.mbarrier::complete_tx::bytes.L2::cache_hint [%0], [%1, {%3, %4, %5}], [%2], %6;"
                 ::"r"(dst), "l"(tm), "r"(bar), "r"(c0), "r"(c1), "r"(c2), "l"(EVICT_FIRST) : "memory");
}
__device__ __forceinline__ void tma2d(uint32_t dst, const CUtensorMap* tm, int c0, int c1, uint32_t bar) {
    asm volatile("cp.async.bulk.tensor.2d.shared::cluster.global.mbarrier::complete_tx::bytes.L2::cache_hint [%0], [%1, {%3, %4}], [%2], %5;"
                 ::"r"(dst), "l"(tm), "r"(bar), "r"(c0), "r"(c1), "l"(EVICT_FIRST) : "memory");
}
__device__ __forceinline__ void tma2dn(uint32_t dst, const CUtensorMap* tm, int c0, int c1, uint32_t bar) {
    asm volatile("cp.async.bulk.tensor.2d.shared::cluster.global.mbarrier::complete_tx::bytes [%0], [%1, {%3, %4}], [%2];"
                 ::"r"(dst), "l"(tm), "r"(bar), "r"(c0), "r"(c1) : "memory");
}
__device__ __forceinline__ void bulk_g2s(uint32_t dst, const void* src, uint32_t bytes, uint32_t bar) {
    asm volatile("cp.async.bulk.shared::cluster.global.mbarrier::complete_tx::bytes [%0], [%1], %2, [%3];" ::"r"(dst), "l"(src), "r"(bytes), "r"(bar) : "memory");
}
__device__ __forceinline__ void ldsm4(uint32_t a, uint32_t (&r)[4]) {
    asm volatile("ldmatrix.sync.aligned.m8n8.x4.shared.b16 {%0,%1,%2,%3}, [%4];" : "=r"(r[0]), "=r"(r[1]), "=r"(r[2]), "=r"(r[3]) : "r"(a) : "memory");
}
__device__ __forceinline__ void ldsm4t(uint32_t a, uint32_t (&r)[4]) {
    asm volatile("ldmatrix.sync.aligned.m8n8.x4.trans.shared.b16 {%0,%1,%2,%3}, [%4];" : "=r"(r[0]), "=r"(r[1]), "=r"(r[2]), "=r"(r[3]) : "r"(a) : "memory");
}
__device__ __forceinline__ void stsm4(uint32_t a, uint32_t x, uint32_t y, uint32_t z, uint32_t w) {
    asm volatile("stmatrix.sync.aligned.m8n8.x4.shared.b16 [%0], {%1,%2,%3,%4};" ::"r"(a), "r"(x), "r"(y), "r"(z), "r"(w) : "memory");
}
__device__ __forceinline__ void mma16816(float (&d)[4], uint32_t a0, uint32_t a1, uint32_t a2, uint32_t a3, uint32_t b0, uint32_t b1) {
    asm volatile("mma.sync.aligned.m16n8k16.row.col.f32.bf16.bf16.f32 {%0,%1,%2,%3}, {%4,%5,%6,%7}, {%8,%9}, {%0,%1,%2,%3};"
        : "+f"(d[0]), "+f"(d[1]), "+f"(d[2]), "+f"(d[3]) : "r"(a0), "r"(a1), "r"(a2), "r"(a3), "r"(b0), "r"(b1));
}
__device__ __forceinline__ void mma_sp(float (&d)[4], const uint32_t (&a)[4], const uint32_t (&b)[4]) {
    asm volatile("mma.sp::ordered_metadata.sync.aligned.m16n8k32.row.col.f32.bf16.bf16.f32 {%0,%1,%2,%3}, {%4,%5,%6,%7}, {%8,%9,%10,%11}, {%12,%12,%12,%12}, %13, 0x0;"
        : "=f"(d[0]), "=f"(d[1]), "=f"(d[2]), "=f"(d[3])
        : "r"(a[0]), "r"(a[1]), "r"(a[2]), "r"(a[3]), "r"(b[0]), "r"(b[1]), "r"(b[2]), "r"(b[3]), "f"(0.f), "r"(0xEEEE4444u));
}
__device__ __forceinline__ uint32_t badd2v(uint32_t a, uint32_t b) { uint32_t d; asm volatile("add.rn.bf16x2 %0, %1, %2;" : "=r"(d) : "r"(a), "r"(b)); return d; }
__device__ __forceinline__ uint32_t negv(uint32_t a) { uint32_t d; asm volatile("xor.b32 %0, %1, 0x80008000;" : "=r"(d) : "r"(a)); return d; }
__device__ __forceinline__ uint32_t pack2(float lo, float hi) { uint32_t d; asm("cvt.rn.bf16x2.f32 %0, %1, %2;" : "=r"(d) : "f"(hi), "f"(lo)); return d; }
__device__ __forceinline__ float bf_lo(uint32_t v) { return __uint_as_float(v << 16); }
__device__ __forceinline__ float bf_hi(uint32_t v) { return __uint_as_float(v & 0xffff0000u); }
__device__ __forceinline__ float ex2(float x) { float y; asm("ex2.approx.ftz.f32 %0, %1;" : "=f"(y) : "f"(x)); return y; }
__device__ __forceinline__ float rsq(float x) { float y; asm("rsqrt.approx.ftz.f32 %0, %1;" : "=f"(y) : "f"(x)); return y; }
__device__ __forceinline__ void bar_sync(int id, int n) { asm volatile("bar.sync %0, %1;" ::"r"(id), "r"(n) : "memory"); }
__device__ __forceinline__ void bar_arrive(int id, int n) { asm volatile("bar.arrive %0, %1;" ::"r"(id), "r"(n) : "memory"); }
__device__ __forceinline__ unsigned ld_acquire(const unsigned* p) { unsigned v; asm volatile("ld.acquire.gpu.global.u32 %0, [%1];" : "=r"(v) : "l"(p) : "memory"); return v; }
__device__ __forceinline__ void st_release(unsigned* p, unsigned v) { asm volatile("st.release.gpu.global.u32 [%0], %1;" ::"l"(p), "r"(v) : "memory"); }
__device__ __forceinline__ uint4 ld_relaxed4(const uint4* p) {
    uint4 v; asm volatile("ld.relaxed.gpu.global.v4.u32 {%0,%1,%2,%3}, [%4];" : "=r"(v.x), "=r"(v.y), "=r"(v.z), "=r"(v.w) : "l"(p) : "memory"); return v;
}
__device__ __forceinline__ void ld_relaxed4_if(uint4& v, const uint4* p, uint32_t cond) {
    asm volatile("{\n.reg .pred p;\nsetp.ne.u32 p, %5, 0;\n@p ld.relaxed.gpu.global.v4.u32 {%0,%1,%2,%3}, [%4];\n}"
                 : "+r"(v.x), "+r"(v.y), "+r"(v.z), "+r"(v.w) : "l"(p), "r"(cond) : "memory");
}
__device__ __forceinline__ uint32_t collect(const uint4* tp, uint32_t par, uint32_t on) {
    uint32_t t;
    asm volatile("{\n.reg .pred p, q, r;\n.reg .b32 u, c;\n.reg .b64 z;\nmov.b32 c, 0;\nmov.b64 z, 0;\nmov.b32 %0, 0;\nsetp.ne.u32 r, %3, 0;\n"
                 "L_%=:\n@r ld.relaxed.gpu.global.u32 %0, [%1];\nadd.u32 c, c, 1;\nsetp.gt.u32 q, c, %4;\n@q st.global.u32 [z], c;\n"
                 "lop3.b32 u, %0, %2, %3, 0x28;\nsetp.ne.u32 p, u, 0;\nvote.sync.any.pred p, p, -1;\n@p bra.uni L_%=;\n}"
                 : "=&r"(t) : "l"(tp), "r"(par), "r"(on), "n"(SPIN_LIMIT) : "memory");
    return t;
}
__device__ __forceinline__ void fetch_at(uint32_t on, uint32_t tl, uint32_t ld, const uint4* lp, uint32_t id) {
    asm volatile("{\n.reg .pred q, r;\n.reg .b32 t0, t1;\n.reg .b64 g;\n"
                 "A_%=:\nmov.u64 g, %%globaltimer;\ncvt.u32.u64 t0, g;\nsub.u32 t0, t0, %1;\nsetp.lt.s32 q, t0, 0;\n@q bra.uni A_%=;\n"
                 "prmt.b32 t1, %0, t0, %4;\n"
                 "prmt.b32 t1, t1, t1, %4;\n"
                 "prmt.b32 t1, t1, t1, %4;\n"
                 "setp.ne.u32 r, t1, 0;\n@r cp.async.cg.shared.global [%2], [%3], 16;\n}"
                 ::"r"(on), "r"(tl), "r"(ld), "l"(lp), "r"(id) : "memory");
}
__device__ __forceinline__ void st_async_if(uint32_t dst, uint32_t a, uint32_t b, uint32_t c, uint32_t d, uint32_t bar, uint32_t cond) {
    asm volatile("{\n.reg .pred p;\nsetp.ne.u32 p, %6, 0;\n@p st.async.weak.shared::cluster.mbarrier::complete_tx::bytes.v4.b32 [%0], {%1,%2,%3,%4}, [%5];\n}"
                 ::"r"(dst), "r"(a), "r"(b), "r"(c), "r"(d), "r"(bar), "r"(cond) : "memory");
}
__device__ __forceinline__ void red_if(__nv_bfloat16* p, uint32_t a, uint32_t b, uint32_t c, uint32_t d, bool cond) {
    asm volatile("{\n.reg .pred p;\nsetp.ne.u32 p, %5, 0;\n@p red.global.add.noftz.v4.bf16x2 [%0], {%1,%2,%3,%4};\n}"
                 ::"l"(p), "r"(a), "r"(b), "r"(c), "r"(d), "r"((uint32_t)cond) : "memory");
}
__device__ __forceinline__ uint32_t mapa(uint32_t a, uint32_t rank) { uint32_t d; asm volatile("mapa.shared::cluster.u32 %0, %1, %2;" : "=r"(d) : "r"(a), "r"(rank)); return d; }
__device__ __forceinline__ uint32_t f2uv(float x) { uint32_t r; asm volatile("cvt.rzi.u32.f32 %0, %1;" : "=r"(r) : "f"(x)); return r; }
__device__ __forceinline__ void sts16(uint32_t a, uint32_t x) { asm volatile("{\n.reg .b16 h;\ncvt.u16.u32 h, %1;\nst.shared.u16 [%0], h;\n}" ::"r"(a), "r"(x) : "memory"); }
__device__ __forceinline__ void st_v4(uint4* p, uint32_t a, uint32_t b, uint32_t c, uint32_t d) {
    asm volatile("st.relaxed.gpu.global.v4.u32 [%0], {%1,%2,%3,%4};" ::"l"(p), "r"(a), "r"(b), "r"(c), "r"(d) : "memory");
}
__device__ __forceinline__ void st_v4_if(uint4* p, uint32_t a, uint32_t b, uint32_t c, uint32_t d, bool cond) {
    asm volatile("{\n.reg .pred p;\nsetp.ne.u32 p, %5, 0;\n@p st.relaxed.gpu.global.v4.u32 [%0], {%1,%2,%3,%4};\n}"
                 ::"l"(p), "r"(a), "r"(b), "r"(c), "r"(d), "r"((uint32_t)cond) : "memory");
}
__device__ __forceinline__ uint32_t pack2t(float lo, float hi, uint32_t par) {
    return (__byte_perm(__float_as_uint(lo) + ((par ^ 1u) << 16), pack2(0.f, hi), 0x7632) & ~1u) | par;
}
__device__ __forceinline__ void lds128(uint32_t a, uint32_t (&r)[4]) {
    asm volatile("ld.shared.v4.u32 {%0,%1,%2,%3}, [%4];" : "=r"(r[0]), "=r"(r[1]), "=r"(r[2]), "=r"(r[3]) : "r"(a) : "memory");
}
__device__ __forceinline__ float sum4(const uint32_t (&r)[4]) {
    return (__uint_as_float(r[0]) + __uint_as_float(r[1])) + (__uint_as_float(r[2]) + __uint_as_float(r[3]));
}
__device__ __forceinline__ void sts32(uint32_t a, uint32_t x) { asm volatile("st.shared.u32 [%0], %1;" ::"r"(a), "r"(x) : "memory"); }
__device__ __forceinline__ void stsf(uint32_t a, float x) { asm volatile("st.shared.f32 [%0], %1;" ::"r"(a), "f"(x) : "memory"); }
__device__ __forceinline__ void stsf2(uint32_t a, float x, float y) { asm volatile("st.shared.v2.f32 [%0], {%1,%2};" ::"r"(a), "f"(x), "f"(y) : "memory"); }
__device__ __forceinline__ float ldsf(uint32_t a) { float v; asm volatile("ld.shared.f32 %0, [%1];" : "=f"(v) : "r"(a) : "memory"); return v; }
__device__ __forceinline__ float2 ldsf2(uint32_t a) { float2 v; asm volatile("ld.shared.v2.f32 {%0,%1}, [%2];" : "=f"(v.x), "=f"(v.y) : "r"(a) : "memory"); return v; }
__device__ __forceinline__ uint32_t lds32(uint32_t a) { uint32_t v; asm volatile("ld.shared.u32 %0, [%1];" : "=r"(v) : "r"(a) : "memory"); return v; }
__device__ __forceinline__ uint32_t ldsv32(uint32_t a) { uint32_t v; asm volatile("ld.volatile.shared.u32 %0, [%1];" : "=r"(v) : "r"(a) : "memory"); return v; }
__device__ __forceinline__ float warp_max(float x) {
    int k = __float_as_int(x);
    k = __reduce_max_sync(0xffffffffu, k ^ ((k >> 31) & 0x7fffffff));
    return __int_as_float(k ^ ((k >> 31) & 0x7fffffff));
}
__device__ __forceinline__ uint32_t now_ns() { uint32_t t; asm volatile("mov.u32 %0, %globaltimer_lo;" : "=r"(t) :: "memory"); return t; }
__device__ __forceinline__ uint32_t clk32() { uint32_t t; asm volatile("mov.u32 %0, %clock;" : "=r"(t) :: "memory"); return t; }
__device__ __forceinline__ void sched_fence(uint32_t& sink) { uint64_t t; asm volatile("mov.u64 %0, %clock64;" : "=l"(t) :: "memory"); sink ^= (uint32_t)(t >> 32); }
__device__ __forceinline__ void sink_if(uint32_t addr, uint32_t sink, uint32_t cond) {
    asm volatile("{\n.reg .pred p;\nsetp.ne.u32 p, %2, 0;\n@p st.shared.u32 [%0], %1;\n}" ::"r"(addr), "r"(sink), "r"(cond) : "memory");
}
__device__ __forceinline__ void sink128_if(uint32_t addr, uint32_t x, bool cond) {
    asm volatile("{\n.reg .pred p;\nsetp.ne.u32 p, %2, 0;\n@p st.shared.v4.u32 [%0], {%1,%3,%3,%3};\n}" ::"r"(addr), "r"(x), "r"((uint32_t)cond), "r"(0) : "memory");
}
__device__ __forceinline__ uint32_t opaque(uint32_t v, int lane) { return __shfl_sync(0xffffffffu, v, lane); }

__device__ __forceinline__ void el_arrive(uint32_t bar) {
    asm volatile("{\n.reg .pred p;\nelect.sync _|p, -1;\n@p mbarrier.arrive.shared::cta.b64 _, [%0];\n}" ::"r"(bar) : "memory");
}
__device__ __forceinline__ void el_expect_tx(uint32_t bar, uint32_t bytes) {
    asm volatile("{\n.reg .pred p;\nelect.sync _|p, -1;\n@p mbarrier.arrive.expect_tx.shared::cta.b64 _, [%0], %1;\n}" ::"r"(bar), "r"(bytes) : "memory");
}
__device__ __forceinline__ void el_tile(uint32_t cb, int s, int t, const CUtensorMap* tm0, const CUtensorMap* tm1) {
    asm volatile("{\n.reg .pred p;\nelect.sync _|p, -1;\n"
                 "@p cp.async.bulk.tensor.3d.shared::cluster.global.mbarrier::complete_tx::bytes.L2::cache_hint [%0], [%1, {%9, %4, %5}], [%3], %7;\n"
                 "@p cp.async.bulk.tensor.2d.shared::cluster.global.mbarrier::complete_tx::bytes.L2::cache_hint [%8], [%2, {%9, %6}], [%3], %7;\n}"
                 ::"r"(SB + s * STAGE_BYTES), "l"(tm0), "l"(tm1), "r"(BAR_FULL + 8 * s), "r"((t & 15) * 96), "r"((t >> 4) * 2), "r"(t * 48),
                   "l"(EVICT_FIRST), "r"(SB + s * STAGE_BYTES + 24576), "r"(0) : "memory");
}
__device__ __forceinline__ void el_bulk(uint32_t dst, const void* src, uint32_t bytes, uint32_t bar) {
    asm volatile("{\n.reg .pred p;\nelect.sync _|p, -1;\n"
                 "@p cp.async.bulk.shared::cluster.global.mbarrier::complete_tx::bytes [%0], [%1], %2, [%3];\n}" ::"r"(dst), "l"(src), "r"(bytes), "r"(bar) : "memory");
}
__device__ __forceinline__ void issue_tile(uint32_t cb, int s, int t, const CUtensorMap* tm0, const CUtensorMap* tm1) {
    const uint32_t bar = BAR_FULL + 8 * s;
    mbar_expect_tx(bar, STAGE_BYTES);
    tma3d(SB + s * STAGE_BYTES, tm0, 0, (t & 15) * 96, (t >> 4) * 2, bar);
    tma2d(SB + s * STAGE_BYTES + 24576, tm1, 0, t * 48, bar);
}

__global__ void __cluster_dims__(CL, 1, 1) __launch_bounds__(384, 1)
fused_kernel(uint64_t scn  , const __nv_bfloat16* __restrict__ q,
             const char* f0, const char* f1, const char* wq, const char* wk,
             const __grid_constant__ CUtensorMap tm0, const __grid_constant__ CUtensorMap tm1,
             const __grid_constant__ CUtensorMap tmq, const __grid_constant__ CUtensorMap tmk,
             const __grid_constant__ CUtensorMap tmv, const __grid_constant__ CUtensorMap tmo,
             __nv_bfloat16* __restrict__ out, const uint4* scl) {
    extern __shared__ __align__(1024) char smem_raw[];
    const int tid = threadIdx.x, warp = tid >> 5, lane = tid & 31;
    const int bid = blockIdx.x, e0 = bid - NSERV;
    const uint32_t cb0 = smem_u32(smem_raw) - K_SB;

    Scratch* const sc = reinterpret_cast<Scratch*>(scn & ~(uint64_t)127);
    [[maybe_unused]] const uint32_t cb = cb0;
    const int NS = ((int)scn & 127) + 1;
    const int NE = NS - NSERV, src = bid;
    int ticket = 0;
    asm volatile("{\n.reg .pred p, s;\n.reg .b32 a, b;\n.reg .b64 x, y;\nsetp.ne.u32 p, %8, 256;\nsetp.lt.s32 s, %9, 0;\n@p bra N_%=;\n@s bra.uni V_%=;\n"
                 "and.b32 a, %9, -16;\nadd.u32 a, a, %9;\nmad.wide.u32 x, a, 12288, %1;\nmad.wide.u32 y, %9, 6144, %2;\n"
                 "cp.async.bulk.prefetch.L2.global.L2::cache_hint [x], 12288, %6;\ncp.async.bulk.prefetch.L2.global.L2::cache_hint [y], 6144, %6;\n"
                 "cp.async.bulk.prefetch.L2.global.L2::cache_hint [x+196608], 12288, %6;\n"
                 "bra E_%=;\n"
                 "V_%=:\nadd.u32 b, %9, %10;\nmad.wide.u32 x, b, 512, %5;\ncp.async.bulk.prefetch.L2.global [x], 512;\n"
                 "mad.wide.u32 x, b, 6144, %4;\ncp.async.bulk.prefetch.L2.global [x], 6144;\n"
                 "mad.wide.u32 y, b, 6144, %3;\ncp.async.bulk.prefetch.L2.global [y], 6144;\nbra E_%=;\n"
                 "N_%=:\nsetp.eq.u32 p, %8, 288;\n@p ld.relaxed.gpu.global.u32 %0, [%7];\nE_%=:\n}"
                 : "+r"(ticket) : "l"(f0), "l"(f1), "l"(wq), "l"(wk), "l"(q), "l"(EVICT_FIRST), "l"(&sc->epoch), "r"(tid), "r"(e0), "n"(NSERV) : "memory");
    if (tid == 320) {
        mbar_init(BAR_FULL, 2);
        if (e0 >= 0) {
            issue_tile(cb, 0, e0, &tm0, &tm1);
        } else {
#pragma unroll
            for (int i = 0; i < 5; ++i) mbar_init(BAR_JOB + 8 * i, 1);
            mbar_expect_tx(BAR_JOB, 32 * CH * 2);
            bulk_g2s(SM_Q, q, 16 * CH * 2, BAR_JOB);
            tma2dn(SM_WK, &tmk, 0, bid * 48, BAR_JOB);
#pragma unroll
            for (int c = 0; c < 3; ++c) {
                mbar_expect_tx(BAR_JOB + 8 + 8 * c, 64 * CH * 2);
                tma2dn(SM_WQ + c * 64 * CH * 2, &tmq, 0, c * 192, BAR_JOB + 8 + 8 * c);
            }
        }
    } else if (tid == 0) {
#pragma unroll
        for (int i = 1; i < 2 * STAGES + 4; ++i)
            mbar_init(BAR_FULL + 8 * i, i < STAGES ? 2 : 1);
        mbar_expect_tx(BAR_V, CL * 768);
        asm volatile("fence.mbarrier_init.release.cluster;" ::: "memory");
    } else if (warp == 1) {
        stsf2(SM_ZERO + lane * 8, 0.f, 0.f);
        if (lane < 4) stsf2(SM_EP + lane * 8, 0.f, 0.f);
        if (lane <= STAGES) sts32(SM_INFO + 4 * lane, lane == STAGES - 1);
        spin_guard((smem_u32(smem_raw) & 0xffffffu) == K_SB ? 0u : ~0u);
    }
    __syncthreads();
    asm volatile("barrier.cluster.arrive.relaxed.aligned;" ::: "memory");

    const int g = lane >> 2, j = lane & 3, m4 = lane >> 3, r8 = lane & 7;

    if (e0 < 0) {
        if (tid == 320) {
            mbar_expect_tx(BAR_JOB + 32, (CH + 16) * CH * 2);
            tma2dn(SM_WO, &tmo, bid * 16, 0, BAR_JOB + 32);
#pragma unroll
            for (int c = 0; c < 3; ++c) tma2dn(SM_WV + c * 64 * CH * 2, &tmv, 0, c * 192, BAR_JOB + 32);
        }
        if (tid == 288) sts32(SM_EP, ticket + 1);
        if (warp == 9) st_v4(&sc->qk[bid * 32 + lane], __shfl_sync(0xffffffffu, ticket, 0), 0u, 0u, 0u);
        st_v4_if(reinterpret_cast<uint4*>(sc->flagW) + bid * 2 + (tid & 1), 0u, 0u, 0u, 0u, tid < 2);
        __syncwarp();
        mbar_wait(BAR_JOB, 0);
        if (warp == 10) {
            uint32_t t[4];
            lds128(SM_Q + bid * 512 + lane * 16, t);
            st_v4(reinterpret_cast<uint4*>(out) + bid * 32 + lane, t[0], t[1], t[2], t[3]);
        }
        if (warp < 8) {
            const int row = 2 * warp + (lane >> 4), c0 = (lane & 15) * 8;
            float v[3][4];
#pragma unroll
            for (int c = 0; c < 3; ++c) {
                const float2 t = ldsf2(SM_Q + row * 384 + c * 128 + c0);
                v[c][0] = bf_lo(__float_as_uint(t.x)); v[c][1] = bf_hi(__float_as_uint(t.x));
                v[c][2] = bf_lo(__float_as_uint(t.y)); v[c][3] = bf_hi(__float_as_uint(t.y));
            }
            float sum = ((v[0][0] + v[0][1]) + (v[0][2] + v[0][3])) + ((v[1][0] + v[1][1]) + (v[1][2] + v[1][3])) + ((v[2][0] + v[2][1]) + (v[2][2] + v[2][3]));
#pragma unroll
            for (int d = 1; d < 16; d <<= 1) sum += __shfl_xor_sync(0xffffffffu, sum, d);
            const float mean = sum * (1.f / CH);
            float ss[3];
#pragma unroll
            for (int c = 0; c < 3; ++c) {
#pragma unroll
                for (int e = 0; e < 4; ++e) v[c][e] -= mean;
                ss[c] = fmaf(v[c][0], v[c][0], v[c][1] * v[c][1]) + fmaf(v[c][2], v[c][2], v[c][3] * v[c][3]);
            }
            sum = ss[0] + ss[1] + ss[2];
#pragma unroll
            for (int d = 1; d < 16; d <<= 1) sum += __shfl_xor_sync(0xffffffffu, sum, d);
            const float rstd = rsq(sum * (1.f / CH) + LN_EPS);
#pragma unroll
            for (int c = 0; c < 3; ++c)
                stsf2(SM_A + row * 400 + c * 128 + c0, __uint_as_float(pack2(v[c][0] * rstd, v[c][1] * rstd)), __uint_as_float(pack2(v[c][2] * rstd, v[c][3] * rstd)));
        }
        {
            float d[2][2][4];
#pragma unroll
            for (int c = 0; c < 4; ++c) d[0][0][c] = d[0][1][c] = d[1][0][c] = d[1][1][c] = 0.f;
            uint32_t a[12][4], qa[4];
#pragma unroll
            for (int k = 0; k < 12; ++k) {
                const int r = 3 * ((m4 & 1) * 8 + r8) + (k >> 2);
                ldsm4(SM_WK + r * 128 + ((((k & 3) * 2 + (m4 >> 1)) ^ (r & 7)) << 4), a[k]);
            }
            mbar_wait(BAR_JOB + 8 + 8 * (warp >> 2), 0);
#pragma unroll
            for (int k = 0; k < 12; ++k) {
                uint32_t b[4];
                const int r = 3 * ((m4 >> 1) * 8 + r8) + (k >> 2);
                ldsm4(SM_WQ + warp * 6144 + r * 128 + ((((k & 3) * 2 + (m4 & 1)) ^ (r & 7)) << 4), b);
                mma16816(d[0][k & 1], a[k][0], a[k][1], a[k][2], a[k][3], b[0], b[1]);
                mma16816(d[1][k & 1], a[k][0], a[k][1], a[k][2], a[k][3], b[2], b[3]);
            }
            bar_sync(1, 384);
            ldsm4(SM_A + ((m4 & 1) * 8 + r8) * 400 + (16 * warp + (m4 >> 1) * 8) * 2, qa);
#pragma unroll
            for (int nb = 0; nb < 2; ++nb) {
                uint32_t hi[2], lo[2];
#pragma unroll
                for (int t = 0; t < 2; ++t) {
                    const float v0 = d[t][0][2 * nb] + d[t][1][2 * nb], v1 = d[t][0][2 * nb + 1] + d[t][1][2 * nb + 1];
                    hi[t] = pack2(v0, v1);
                    lo[t] = pack2(v0 - bf_lo(hi[t]), v1 - bf_hi(hi[t]));
                }
                float e[4] = {0.f, 0.f, 0.f, 0.f};
                mma16816(e, qa[0], qa[1], qa[2], qa[3], hi[0], hi[1]);
                mma16816(e, qa[0], qa[1], qa[2], qa[3], lo[0], lo[1]);
                stsm4(SM_RED + (warp * 2 + nb) * 512 + lane * 16, __float_as_uint(e[0]), __float_as_uint(e[1]), __float_as_uint(e[2]), __float_as_uint(e[3]));
            }
            bar_sync(1, 384);
            if (warp == 0) {
                float r[8] = {0.f, 0.f, 0.f, 0.f, 0.f, 0.f, 0.f, 0.f};
#pragma unroll
                for (int u = 0; u < 24; ++u) {
                    uint32_t e[4];
                    ldsm4(SM_RED + u * 512 + lane * 16, e);
#pragma unroll
                    for (int c = 0; c < 4; ++c) r[(u & 1) * 4 + c] += __uint_as_float(e[c]);
                }
                const float qs = 1.4426950408889634f * 13.856406460551018f;
                const uint32_t a0 = pack2t(r[0] * qs, r[1] * qs, lds32(SM_EP) & 1u), a1 = pack2(r[2] * qs, r[3] * qs);
                const uint32_t a2 = pack2(r[4] * qs, r[5] * qs), a3 = pack2(r[6] * qs, r[7] * qs);
                st_v4(&sc->qk[bid * 32 + lane], a0, a1, a2, a3);
            }
        }
        {
            mbar_wait(BAR_JOB + 32, 0);
            float d[2][4] = {{0.f, 0.f, 0.f, 0.f}, {0.f, 0.f, 0.f, 0.f}};
#pragma unroll 1
            for (int k = 0; k < 12; ++k) {
                uint32_t a[4], b[4];
                ldsm4t(SM_WO + (16 * k + (m4 >> 1) * 8 + r8) * 32 + (m4 & 1) * 16, a);
                const int r = 3 * ((m4 >> 1) * 8 + r8) + (k >> 2);
                ldsm4(SM_WV + warp * 6144 + r * 128 + ((((k & 3) * 2 + (m4 & 1)) ^ (r & 7)) << 4), b);
                mma16816(d[0], a[0], a[1], a[2], a[3], b[0], b[1]);
                mma16816(d[1], a[0], a[1], a[2], a[3], b[2], b[3]);
            }
            float s0 = (d[0][0] + d[0][1]) + (d[1][0] + d[1][1]), s1 = (d[0][2] + d[0][3]) + (d[1][2] + d[1][3]);
            s0 += __shfl_xor_sync(0xffffffffu, s0, 1); s1 += __shfl_xor_sync(0xffffffffu, s1, 1);
            s0 += __shfl_xor_sync(0xffffffffu, s0, 2); s1 += __shfl_xor_sync(0xffffffffu, s1, 2);
            if (j == 0) stsf2(SM_FW + (warp * 8 + g) * 8, s0, s1);
            bar_sync(1, 384);
            s0 = s1 = 0.f;
#pragma unroll 1
            for (int u = 0; u < 12; ++u) { const float2 t = ldsf2(SM_FW + (u * 8 + g) * 8); s0 += t.x; s1 += t.y; }
            s0 *= 1.f / CH; s1 *= 1.f / CH;
            const int h = bid / 3, i = (warp + 12 - 3 * h) % 12;
            uint32_t* wp = &sc->wvo[(((i >> 2) * 4 + h) * 12 + (i & 3) * 3 + bid % 3) * 128 + lane];
            wp[0] = pack2(d[0][0] - s0, d[0][1] - s0); wp[32] = pack2(d[1][0] - s0, d[1][1] - s0);
            wp[64] = pack2(d[0][2] - s1, d[0][3] - s1); wp[96] = pack2(d[1][2] - s1, d[1][3] - s1);
            asm volatile("fence.proxy.async;" ::: "memory");
            bar_sync(1, 384);
            if (tid == 0) st_release(&sc->flagW[bid * 8], lds32(SM_EP));
        }
    }

    if (warp < 4) {
        asm volatile("setmaxnreg.inc.sync.aligned.u32 176;");
        const uint32_t cb = opaque(cb0, lane);
        const int w = warp;
        uint32_t oa[6], ob[6];
#pragma unroll
        for (int b = 0; b < 3; ++b) {
            int r = 3 * (8 * w + r8) + b;
            uint32_t o = SB + r * 128 + ((m4 ^ (r & 7)) << 4);
            oa[2 * b] = opaque(o, lane); oa[2 * b + 1] = opaque(o ^ 64u, lane);
            r = 3 * (4 * w + (r8 >> 1)) + b;
            o = SB + 24576 + r * 128 + ((m4 ^ 1 ^ (r & 7)) << 4);
            ob[2 * b] = opaque(o, lane); ob[2 * b + 1] = opaque(o ^ 64u, lane);
        }
        uint32_t one[4][2];
#pragma unroll
        for (int i = 0; i < 4; ++i) {
            one[i][0] = 0x3F803F80u + lds32(SM_ZERO + (lane + 2 * i) * 4); one[i][1] = 0x3F803F80u + lds32(SM_ZERO + (lane + 2 * i + 1) * 4);
        }
        const uint32_t dmask = opaque(j == (g >> 1) ? 0xffff0000u : 0u, lane);
        const float dsel = __uint_as_float(opaque(j == (g >> 1) ? 0x3f800000u : 0u, lane));
        const bool odd = opaque(g & 1, lane) != 0;
        uint32_t first = 0;
        const uint32_t pst = opaque(SM_P + w * 512 + lane * 16, lane);
        const uint32_t lst = opaque(SM_UL + 256 + (j & 1) * 128 + g * 16 + w * 4, lane), loff = opaque(((g * 128 + src) * 2 + (j & 1)) * 16, lane);
        const bool odj = lst & 128;
        uint32_t qk[12][4];
#pragma unroll
        for (int k = 0; k < 12; ++k) qk[k][0] = qk[k][1] = qk[k][2] = qk[k][3] = 0u;
        float R0 = 0.f, R1 = 0.f;
        float m0 = -INFINITY, m1 = -INFINITY, l0 = 0.f, l1 = 0.f;
        int s = STAGES - 1; uint32_t st = (STAGES - 1) * STAGE_BYTES, ph = 1, pbuf = 0;
        uint32_t sink = lds32(SM_ZERO + (lane + 8) * 4), seq = 0;
        mbar_wait(BAR_EP, 0);
#pragma unroll 1
        while (true) {
            mbar_wait(BAR_FULL + 8 * s, ph);
            uint32_t r0[6][4], r1[6][4], f[6][4];
            float S2[2][2][4], T2[2][2][4];
#pragma unroll
            for (int b = 0; b < 2; ++b)
#pragma unroll
                for (int c = 0; c < 4; ++c) { S2[0][b][c] = S2[1][b][c] = 0.f; T2[0][b][c] = T2[1][b][c] = 0.f; }
            uint32_t d0[2][2], d1[2][2];
#pragma unroll
            for (int n = 0; n < 2; ++n) { ldsm4(st + ob[n], f[n]); ldsm4(st + oa[n], r0[n]); ldsm4(st + oa[n] + 12288, r1[n]); }
            sched_fence(sink);
#pragma unroll
            for (int k = -1; k < 12; ++k) {
                const int n = (k + 1) / 2 + 2;
                if (n < 6) {
                    if ((k + 1) & 1) ldsm4(st + oa[n] + 12288, r1[n]);
                    else { ldsm4(st + ob[n], f[n]); ldsm4(st + oa[n], r0[n]); }
                }
                if (k == ORDER_AT) bar_arrive(8, 256);
                if (k >= 0) {
                    const int i = k >> 1, h = k & 1;
                    mma16816(T2[h][0], d0[h][0], one[h][0], d0[h][1], one[h][1], r0[i][2 * h], r0[i][2 * h + 1]);
                    mma16816(T2[h][1], d1[h][0], one[2 + h][0], d1[h][1], one[2 + h][1], r1[i][2 * h], r1[i][2 * h + 1]);
                    mma16816(S2[h][0], qk[k][0], qk[k][1], qk[k][2], qk[k][3], r0[i][2 * h], r0[i][2 * h + 1]);
                    mma16816(S2[h][1], qk[k][0], qk[k][1], qk[k][2], qk[k][3], r1[i][2 * h], r1[i][2 * h + 1]);
                }
                if (k < 11) {
                    const int i = (k + 1) >> 1, h = (k + 1) & 1;
#pragma unroll
                    for (int c = 0; c < 2; ++c) {
                        r0[i][2 * h + c] = badd2v(r0[i][2 * h + c], f[i][2 * h + (c ^ 1)]); r1[i][2 * h + c] = badd2v(r1[i][2 * h + c], f[i][2 * h + (c ^ 1)]);
                        d0[h][c] = negv(r0[i][2 * h + c]); d1[h][c] = negv(r1[i][2 * h + c]);
                    }
                    sched_fence(sink);
                }
            }
            float S[2][4], T[2][4];
#pragma unroll
            for (int b = 0; b < 2; ++b)
#pragma unroll
                for (int c = 0; c < 4; ++c) { S[b][c] = S2[0][b][c] + S2[1][b][c]; T[b][c] = T2[0][b][c] + T2[1][b][c]; }
            uint32_t rb[2];
#pragma unroll
            for (int b = 0; b < 2; ++b) {
                const float qd = odd ? T[b][1] : T[b][0], sd = odd ? T[b][3] : T[b][2];
                const float rd = rsq(fmaxf(fmaf(qd, -(float)CH, fmaf(-sd, sd, EPS2)), EPS2));
                const float hi = __uint_as_float(__float_as_uint(rd) & dmask);
                rb[b] = pack2(fmaf(rd, dsel, -hi), hi);
            }
            float rs[4] = {0.f, 0.f, 0.f, 0.f};
            mma16816(rs, 0x3F803F80u, 0u, 0u, 0x3F803F80u, rb[0], rb[1]);
            float y[2][4], z[2][4], p[2][4];
            uint32_t pp[4];
#pragma unroll
            for (int b = 0; b < 2; ++b) {
                y[b][0] = fmaf(-T[b][2], R0, S[b][0]); y[b][1] = fmaf(-T[b][3], R0, S[b][1]);
                y[b][2] = fmaf(-T[b][2], R1, S[b][2]); y[b][3] = fmaf(-T[b][3], R1, S[b][3]);
            }
            auto softmax_p = [&](uint32_t pb) {
#pragma unroll
                for (int b = 0; b < 2; ++b) {
                    z[b][0] = fmaf(rs[2 * b], y[b][0], -m0); z[b][1] = fmaf(rs[2 * b + 1], y[b][1], -m0);
                    z[b][2] = fmaf(rs[2 * b], y[b][2], -m1); z[b][3] = fmaf(rs[2 * b + 1], y[b][3], -m1);
#pragma unroll
                    for (int c = 0; c < 4; ++c) p[b][c] = ex2(z[b][c]);
                    pp[2 * b] = pack2(p[b][0] * rs[2 * b], p[b][1] * rs[2 * b + 1]);
                    pp[2 * b + 1] = pack2(p[b][2] * rs[2 * b], p[b][3] * rs[2 * b + 1]);
                }
                stsm4(pst + pb, pp[0], pp[1], pp[2], pp[3]);
            };
            softmax_p(pbuf);
            const float zmax = fmaxf(fmaxf(fmaxf(z[0][0], z[0][1]), fmaxf(z[0][2], z[0][3])), fmaxf(fmaxf(z[1][0], z[1][1]), fmaxf(z[1][2], z[1][3])));
            ++seq;
            sink_if(SM_FLAG + (pbuf >> 9), seq, zmax > RESCALE_TH);
            const uint32_t info = lds32(SM_INFO + 4 * s);
            bar_sync(1, 256);
            const float k0 = l0, k1 = l1;
            l0 += (p[0][0] + p[0][1]) + (p[1][0] + p[1][1]);
            l1 += (p[0][2] + p[0][3]) + (p[1][2] + p[1][3]);
            const uint32_t flag = lds32(SM_FLAG + (pbuf >> 9));
            mbar_arrive_if(BAR_EMPTY + 8 * s, first);
            pbuf ^= 2048;
            st += STAGE_BYTES;
            if (++s == STAGES) { s = 0; st = 0; ph ^= 1; }
            auto hand_over = [&]() {
                const float e = (odj ? l1 : l0) + __shfl_xor_sync(0xffffffffu, odj ? l0 : l1, 1);
                stsf(lst, (e + __shfl_xor_sync(0xffffffffu, e, 2)) * (1.f / CH));
            };
            if (info & 1) hand_over();
            if (flag != seq && !(info & 3)) continue;
            if (flag == seq) {
                const int tz = tid + lds32(SM_EP + 4), w = tz >> 5, g = tz >> 2 & 7, j = tz & 3;
                float x0 = fmaxf(fmaxf(rs[0] * y[0][0], rs[1] * y[0][1]), fmaxf(rs[2] * y[1][0], rs[3] * y[1][1]));
                float x1 = fmaxf(fmaxf(rs[0] * y[0][2], rs[1] * y[0][3]), fmaxf(rs[2] * y[1][2], rs[3] * y[1][3]));
                x0 = fmaxf(x0, __shfl_xor_sync(0xffffffffu, x0, 1)); x0 = fmaxf(x0, __shfl_xor_sync(0xffffffffu, x0, 2));
                x1 = fmaxf(x1, __shfl_xor_sync(0xffffffffu, x1, 1)); x1 = fmaxf(x1, __shfl_xor_sync(0xffffffffu, x1, 2));
                stsf(SM_MX + (w * 16 + g + (j & 1) * 8) * 4, (j & 1) ? x1 : x0);
                bar_sync(2, 128);
                float n0 = m0, n1 = m1;
#pragma unroll
                for (int u = 0; u < 4; ++u) { n0 = fmaxf(n0, ldsf(SM_MX + (u * 16 + g) * 4)); n1 = fmaxf(n1, ldsf(SM_MX + (u * 16 + g + 8) * 4)); }
                n0 = ceilf(n0); n1 = ceilf(n1);
                const float a0 = ex2(m0 - n0), a1 = ex2(m1 - n1);
                m0 = n0; m1 = n1;
                stsf(SM_AL + j * 32 + g * 4, j == 0 ? a0 : j == 1 ? a1 : j == 2 ? n0 : n1);
                bar_arrive(3, 256);
                softmax_p(pbuf ^ 2048);
                bar_sync(1, 256);
                l0 = fmaf(k0, a0, (p[0][0] + p[0][1]) + (p[1][0] + p[1][1]));
                l1 = fmaf(k1, a1, (p[0][2] + p[0][3]) + (p[1][2] + p[1][3]));
                if (info & 1) hand_over();
            }
            if (info & 2) {
                s += 3; st += 3 * STAGE_BYTES;
                if (s >= STAGES) { s -= STAGES; st -= STAGES * STAGE_BYTES; ph ^= 1; }
            }
            if (!(info & 1)) continue;
            if (seq != 1 && warp != 0) {
                bar_arrive(2, 128);
                return;
            }
            const uint32_t epoch = lds32(SM_EP), mt = (__float_as_uint(m0) & ~1u) | ((epoch ^ (seq == 1)) & 1u);
            bar_sync(2, 128);
            {
                uint32_t la[4], lb[4];
                lds128(lst & ~140u, la); lds128((lst & ~140u) + 128, lb);
                const float sa = sum4(la), sb = sum4(lb);
                const float ha = __uint_as_float(__float_as_uint(sa) & 0xffff0000u), hb = __uint_as_float(__float_as_uint(sb) & 0xffff0000u);
                st_v4(reinterpret_cast<uint4*>(reinterpret_cast<char*>(sc->L) + loff), pack2(ha, sa - ha), pack2(hb, sb - hb), mt, __float_as_uint(m1));
            }
            if (seq != 1) return;
            sink_if(SM_EP + 8, sink, lds32(SM_EP + 4));
            m0 = m1 = -INFINITY; l0 = l1 = 0.f;
            const int tz = tid + lds32(SM_EP + 4), w = tz >> 5, lane = tz & 31;
            uint4 v[3];
            unsigned it = 0;
            while (true) {
                if (it < 2 && src >= NSERV) mbar_wait(BAR_FULL + 8 * (QK_AFTER + it), 0);
#pragma unroll
                for (int k = 0; k < 3; ++k) v[k] = ld_relaxed4(&sc->qk[(3 * w + k) * 32 + lane]);
                const uint32_t bad = (v[0].x ^ epoch) | (v[1].x ^ epoch) | (v[2].x ^ epoch);
                if (__all_sync(0xffffffffu, (bad & 1u) == 0)) break;
                spin_guard(++it);
            }
            bar_sync(6, 256);
#pragma unroll
            for (int k = 0; k < 3; ++k) stsm4(SM_XA + (3 * w + k) * 512 + lane * 16, v[k].x, v[k].y, v[k].z, v[k].w);
            bar_sync(2, 128);
#pragma unroll
            for (int k = 0; k < 12; ++k) ldsm4(SM_XA + k * 512 + lane * 16, qk[k]);
            asm volatile("fence.proxy.async.shared::cta;" ::: "memory");
            bar_sync(2, 128);
            mbar_arrive_if(BAR_EMPTY + 8 * (STAGES - 1), tz == 0);
            first = tz == 0;
            float r[4] = {0.f, 0.f, 0.f, 0.f}, r2[4] = {0.f, 0.f, 0.f, 0.f};
#pragma unroll
            for (int k = 0; k < 12; k += 2) {
                mma16816(r, qk[k][0], qk[k][1], qk[k][2], qk[k][3], 0x3F803F80u, 0x3F803F80u);
                mma16816(r2, qk[k + 1][0], qk[k + 1][1], qk[k + 1][2], qk[k + 1][3], 0x3F803F80u, 0x3F803F80u);
            }
            R0 = (r[0] + r2[0]) * (1.f / CH); R1 = (r[2] + r2[2]) * (1.f / CH);
        }
    } else if (warp < 8) {
        asm volatile("setmaxnreg.inc.sync.aligned.u32 256;");
        const uint32_t cb = opaque(cb0, lane);
        pad<4>();
        const int h = __shfl_sync(0xffffffffu, warp - 4, 0);
        uint32_t oa[3], ob[3];
#pragma unroll
        for (int b = 0; b < 3; ++b) {
            int cc = 6 * h + 2 * b + (m4 >> 1);
            int r = 3 * r8 + (cc >> 3);
            oa[b] = opaque(SB + (m4 & 1) * 12288 + r * 128 + (((cc & 7) ^ (r & 7)) << 4), lane);
            cc = 6 * h + 2 * b + (m4 & 1);
            r = 3 * (4 * (m4 >> 1) + (r8 >> 1)) + (cc >> 3);
            ob[b] = opaque(SB + 24576 + r * 128 + (((cc & 7) ^ (r & 7)) << 4), lane);
        }
        const uint32_t l16 = opaque(lane * 16, lane);
        const uint32_t vdst = opaque(mapa(SM_A + (bid & (CL - 1)) * 832 + h * 192 + ((j ^ (bid >> 1 & 3)) << 4), g), lane), vbar = opaque(mapa(BAR_V, g), lane);
        uint32_t axb = SM_XA;
        float acc[6][4];
#pragma unroll
        for (int t = 0; t < 6; ++t) acc[t][0] = acc[t][1] = acc[t][2] = acc[t][3] = 0.f;
        int s = STAGES - 1; uint32_t ph = 1, pbuf = 0;
        uint32_t wf[12][3][4];
#pragma unroll
        for (int i = 0; i < 12; ++i)
#pragma unroll
            for (int c = 0; c < 4; ++c) wf[i][0][c] = wf[i][1][c] = wf[i][2][c] = 0u;
        uint32_t seq = 0, info = 0, sink = 0;
        mbar_wait(BAR_EP, 0);
        uint32_t par = ~lds32(SM_EP) & 1u;
        st_v4_if(&sc->M[(g * 128 + src) * 2 + (j & 1)], 0u, 0u, par, 0u, ((j & 2) | h) == 0);
#pragma unroll 1
        while (true) {
            if (info & 2) {
                const uint32_t lz = l16 + lds32(SM_EP + 4);
                st_v4_if(&sc->M[((lz >> 6) * 128 + src) * 2 + (lz >> 4 & 1)], 0u, 0u, (lds32(SM_AL + 64 + (lz >> 6 << 2)) & ~1u) | par, lds32(SM_AL + 96 + (lz >> 6 << 2)),
                         ((lz & 32) | h) == 0);
                asm volatile("barrier.cluster.wait.aligned;" ::: "memory");
#pragma unroll
                for (int c = 0; c < 3; ++c) {
                    mbar_wait(BAR_FULL + 8 * s, ph);
#pragma unroll
                    for (int i = 0; i < 12; ++i) ldsm4(SB + s * STAGE_BYTES + (h * 12 + i) * 512 + lz, wf[4 * c + i / 3][i % 3]);
                    bar_sync(4, 128);
                    mbar_arrive_if(BAR_EMPTY + 8 * s, (lz | h) == 0);
                    if (++s == STAGES) { s = 0; ph ^= 1; }
                }
            }
            if (info & 4) {
                float u0 = 0.f, u1 = 0.f;
#pragma unroll
                for (int t = 0; t < 6; ++t) { u0 += acc[t][0] + acc[t][1]; u1 += acc[t][2] + acc[t][3]; }
                const uint32_t lz = l16 + lds32(SM_EP + 4);
                const bool j1 = lz & 16;
                const float e = (j1 ? u1 : u0) + __shfl_xor_sync(0xffffffffu, j1 ? u0 : u1, 1);
                stsf(SM_UL + (lz & 16) * 8 + (lz >> 6 << 4) + h * 4, (e + __shfl_xor_sync(0xffffffffu, e, 2)) * (1.f / CH));
                bar_sync(4, 128);
                uint32_t ua[4], ub[4];
                lds128(SM_UL + (lz >> 6 << 4), ua); lds128(SM_UL + 128 + (lz >> 6 << 4), ub);
                u0 = sum4(ua); u1 = sum4(ub);
#pragma unroll
                for (int t = 0; t < 6; ++t) { acc[t][0] -= u0; acc[t][1] -= u0; acc[t][2] -= u1; acc[t][3] -= u1; }
            }
            auto project = [&]() {
                uint32_t af[12][4], ax[4];
#pragma unroll
                for (int i = 0; i < 4; ++i) ax[i] = axb + ((h + i) & 3) * 1536;
                const uint32_t real = seq != 1;
#pragma unroll
                for (int ks = 0; ks < 3; ++ks) {
                    af[ks][0] = pack2(acc[2 * ks][0], acc[2 * ks][1]); af[ks][1] = pack2(acc[2 * ks][2], acc[2 * ks][3]);
                    af[ks][2] = pack2(acc[2 * ks + 1][0], acc[2 * ks + 1][1]); af[ks][3] = pack2(acc[2 * ks + 1][2], acc[2 * ks + 1][3]);
                    stsm4(ax[0] + ks * 512 + l16, af[ks][0], af[ks][1], af[ks][2], af[ks][3]);
                }
                float o[4][2][4];
                constexpr int ord[36] = {0,1,2,0,1,2,0,1,2, 0,1,0,2,0,1,0,1,0,2,0,1,0,1,0,1,0, 1,2,1,2,1, 2,3,2,3,2};
                int nx[3] = {0, 0, 0};
                bool used3 = false;
#pragma unroll
                for (int z = 0; z < 36; ++z) {
                    const int a = ord[z], tp = a == 3 ? 2 : a, i = nx[tp]++;
                    if (i == 0 || (a == 3 && !used3)) {
#pragma unroll
                        for (int c = 0; c < 4; ++c) o[a][0][c] = o[a][1][c] = 0.f;
                    }
                    if (a == 3) used3 = true;
                    mma16816(o[a][0], af[i][0], af[i][1], af[i][2], af[i][3], wf[i][tp][0], wf[i][tp][1]);
                    mma16816(o[a][1], af[i][0], af[i][1], af[i][2], af[i][3], wf[i][tp][2], wf[i][tp][3]);
                    if (z == 0 || z == 2 || z == 30) sched_fence(sink);
                    if (z == 2) bar_sync(4, 128);
                    if (z == REL_Z) asm volatile("{\n.reg .pred p;\nsetp.ne.u32 p, %0, 0;\n@p bar.arrive 12, 256;\n}" ::"r"(real) : "memory");
#pragma unroll
                    for (int k = 0; k < 9; ++k) if (z == 2) ldsm4(ax[1 + k / 3] + (k % 3) * 512 + l16, af[3 + k]);
#pragma unroll
                    for (int e = 0; e < 3; ++e)
                        if (z == (e == 0 ? 26 : e == 1 ? 31 : 35)) {
                            if (e == 2) {
#pragma unroll
                                for (int c = 0; c < 4; ++c) { o[2][0][c] += o[3][0][c]; o[2][1][c] += o[3][1][c]; }
                            }
                            st_async_if(vdst + e * 64, pack2(o[e][0][0], o[e][0][1]), pack2(o[e][1][0], o[e][1][1]),
                                        pack2(o[e][0][2], o[e][0][3]), pack2(o[e][1][2], o[e][1][3]), vbar, real);
                        }
                }
            };
            if (!(info & 1)) {
                const uint32_t st = __shfl_sync(0xffffffffu, s * STAGE_BYTES, 0);
                axb = SB + st;
                const uint32_t lz = l16 + lds32(SM_EP + 4);
                const char* tp = reinterpret_cast<const char*>(sc->T) + ((lz >> 5 << 12) + (lz & 16) + src * 32);
                uint32_t ann = (lz >> 8 | h) == 0;
                asm volatile("" : "+l"(tp), "+r"(ann));
                mbar_wait(BAR_FULL + 8 * s, ph);
                asm volatile("{\n.reg .pred p;\n.reg .b32 t, u;\nld.shared.u32 %0, [%1];\nmov.u32 t, %%globaltimer_lo;\nlop3.b32 t, t, 1, %3, 0xba;\n"
                             "and.b32 u, %0, %4;\nsetp.ne.u32 p, u, 0;\n@p st.relaxed.gpu.global.v4.u32 [%2], {t,t,t,t};\n}"
                             : "=r"(info) : "r"(SM_INFO + 4 * s), "l"(tp), "r"(par), "r"(ann) : "memory");
                bar_sync(8, 256);
                uint32_t xt[4][3][4];
#pragma unroll
                for (int u = 0; u < 6; ++u) {
                    const int gp = u / 3, b = u % 3;
                    if (u == 5) asm volatile("{\n.reg .pred p;\nsetp.ne.u32 p, %0, 0;\n@p bar.arrive 11, 256;\n}" ::"r"((uint32_t)((info & 1) && seq != 0)) : "memory");
                    uint32_t f[4];
                    ldsm4t(st + ob[b] + gp * 3072, f);
                    ldsm4t(st + oa[b] + (2 * gp) * 3072, xt[2 * gp][b]);
                    ldsm4t(st + oa[b] + (2 * gp + 1) * 3072, xt[2 * gp + 1][b]);
                    if (u == 1 || u == 3) sched_fence(sink);
#pragma unroll
                    for (int c = 0; c < 4; ++c) {
                        xt[2 * gp][b][c] = badd2v(xt[2 * gp][b][c], f[c >> 1]);
                        xt[2 * gp + 1][b][c] = badd2v(xt[2 * gp + 1][b][c], f[2 + (c >> 1)]);
                    }
                }
                ++seq;
                const uint32_t pb = pbuf;
                pbuf ^= 2048;
                if (++s == STAGES) { s = 0; ph ^= 1; }
                auto accumulate = [&]() {
                    uint32_t pa[4][4], fa = SM_FLAG + (pb >> 9);
#pragma unroll 1
                    while (true) {
                        if (fa == SM_EP + 4) {
                            bar_sync(3, 256);
                            const uint32_t gz = (l16 + lds32(SM_EP + 4)) >> 6 << 2;
                            const float a0 = ldsf(SM_AL + gz), a1 = ldsf(SM_AL + 32 + gz);
#pragma unroll
                            for (int t = 0; t < 6; ++t) { acc[t][0] *= a0; acc[t][1] *= a0; acc[t][2] *= a1; acc[t][3] *= a1; }
                        }
                        bar_sync(1, 256);
                        uint32_t flag;
                        asm volatile("ld.shared.u32 %4, [%6];\nldmatrix.sync.aligned.m8n8.x4.shared.b16 {%0,%1,%2,%3}, [%5];"
                                     : "=r"(pa[0][0]), "=r"(pa[0][1]), "=r"(pa[0][2]), "=r"(pa[0][3]), "=r"(flag) : "r"(SM_P + l16 + pb), "r"(fa) : "memory");
                        fa = SM_EP + 4;
                        if (flag != seq) break;
                    }
#pragma unroll
                    for (int gq = 1; gq < 4; ++gq) ldsm4(SM_P + l16 + pb + gq * 512, pa[gq]);
#pragma unroll
                    for (int gq = 0; gq < 4; ++gq)
#pragma unroll
                        for (int b = 0; b < 3; ++b) {
                            mma16816(acc[2 * b], pa[gq][0], pa[gq][1], pa[gq][2], pa[gq][3], xt[gq][b][0], xt[gq][b][1]);
                            mma16816(acc[2 * b + 1], pa[gq][0], pa[gq][1], pa[gq][2], pa[gq][3], xt[gq][b][2], xt[gq][b][3]);
                        }
                };
                if (info != 1) { accumulate(); continue; }
                accumulate();
                project();
            } else {
                project();
            }
            if (seq != 1) break;
            sink_if(SM_EP + 8, sink, lds32(SM_EP + 4));
            asm volatile("fence.proxy.async.shared::cta;" ::: "memory");
            bar_arrive(6, 256);
            par ^= 1u;
            info = 0;
#pragma unroll
            for (int t = 0; t < 6; ++t) acc[t][0] = acc[t][1] = acc[t][2] = acc[t][3] = 0.f;
        }
    } else {
        asm volatile("setmaxnreg.dec.sync.aligned.u32 72;");
        const uint32_t cb = opaque(cb0, lane);
        const int fw = __shfl_sync(0xffffffffu, warp - 8, 0);
        if (fw == 0) {
            if (src < NSERV) {
                el_expect_tx(BAR_FULL, STAGE_BYTES);
                el_tile(cb, 0, JOIN_N * NE + src, &tm0, &tm1);
            }
            el_expect_tx(BAR_FULL + 8, STAGE_BYTES);
            el_tile(cb, 1, src < NSERV ? JOIN_N * NE + NS + src : src - NSERV + NE, &tm0, &tm1);
            el_arrive(BAR_FULL);
        } else if (fw == 1) {
            const unsigned epoch = __shfl_sync(0xffffffffu, ticket + 1, 0);
            sts32(SM_EP, epoch);
            el_arrive(BAR_EP);
            stsf2(SM_FLAG + 8, __uint_as_float(now_ns()), __uint_as_float(clk32()));
            __nanosleep(6000);
            unsigned it = 0;
            while (!__all_sync(0xffffffffu, ld_acquire(sc->flagW + min(lane, NSERV - 1) * 8) == epoch)) { spin_guard(++it); __nanosleep(64); }
            asm volatile("fence.proxy.async;" ::: "memory");
            __syncwarp();
            el_arrive(BAR_W);
        }
        uint32_t sink = 0;
        int slot = 2, n = fw ? 0 : src < NSERV ? JOIN_N + 2 : 2, sp = 1, sd = 0;
        uint32_t pp = 0, pd = 0;
#pragma unroll 1
        for (int real = 0; ; ++real) {
        {
            const int wat = CHECKPOINT + (bid & WSTAG), pause = real ? 0 : PAUSE + (bid >> 4 & 7);
            auto wait_empty = [&](int sl) {
                const int r = (sl * 37) >> 8, st = sl - r * STAGES;
                mbar_wait_u(BAR_EMPTY + 8 * st, (r ^ (st != STAGES - 1)) & 1);
                return st;
            };
            while (n != pause && n != 0) {
                const int t = n < JOIN_N ? src - NSERV + n * NE : n < NSTATIC ? src + n * NS - JOIN_N * NSERV : NSTATIC * NS - JOIN_N * NSERV + __shfl_sync(0xffffffffu, ticket, 0);
                const bool done = t >= NTILES, winj = n == wat || (done && n < wat);
                sts32(SM_INFO + 4 * sp, done + 2 * winj + 4 * ((unsigned)(NTILES - END_X - t) < (unsigned)(2 * NS)));
                sts32(SM_INFO + 4 * STAGES, done ? ~0u : n);
                el_arrive(BAR_FULL + 8 * sp);
                const int wslot = slot;
                if (winj) slot += 3;
                if (!done) {
                    const int s = wait_empty(slot);
                    el_expect_tx(BAR_FULL + 8 * s, STAGE_BYTES);
                    mbar_wait_u(BAR_FULL + 8 * sd, pd);
                    if (n >= MID_FROM || t >= NTILES - END_X) {
                        const uint32_t c0 = clk32(), hold = t >= NTILES - END_X ? D_END : MID_D;
                        while (clk32() - c0 < hold && !mbar_test(BAR_FULL + 8 * sp, pp)) __nanosleep(50);
                    }
                    asm volatile("{\n.reg .pred p;\nsetp.ne.u32 p, %2, 0;\n@p atom.relaxed.gpu.global.inc.u32 %0, [%1], 0x7fffffff;\n}"
                                 : "+r"(ticket) : "l"(&sc->ctr), "r"((uint32_t)(n >= NSTATIC - 1 && lane == 0)) : "memory");
                    el_tile(cb, s, t, &tm0, &tm1);
                    sd = sp; pd = pp; sp = s; pp = ((slot * 37) >> 8) & 1;
                    ++n;
                    if (++slot >= 2 * STAGES) slot -= 2 * STAGES;
                } else {
                    sts32(SM_EP + 12, SB + (slot - ((slot * 37) >> 8) * STAGES) * STAGE_BYTES + sp * 2 + pp + (sd * 2 + (pd ^ (sd == STAGES - 1))) * 16);
                    n = 0;
                }
                if (winj) {
                    mbar_wait_u(BAR_W, 0);
#pragma unroll 1
                    for (int c = 0; c < 3; ++c) {
                        const int st = wait_empty(wslot + c);
                        el_expect_tx(BAR_FULL + 8 * st, 24576);
                        el_bulk(SB + st * STAGE_BYTES, sc->wvo + c * 6144, 24576, BAR_FULL + 8 * st);
                        el_arrive(BAR_FULL + 8 * st);
                    }
                }
            }
        }
        if (fw == 0) bar_arrive(7, 128);
        {
            const int ft = tid - 256 + lds32(SM_EP + 4), lane = ft & 31, g = lane >> 2, j = lane & 3;
            const int n0 = src & (CL - 1);
            const uint32_t epoch = lds32(SM_EP), par = epoch & 1u;
            unsigned it = 0;
            if (fw == 1 && real) {
                const uint4* xp = &(real > 1 ? sc->L : sc->M)[(n0 * 128 + lane) * 2];
                uint4 x[4];
                while ((uint32_t)ldsv32(SM_INFO + 4 * STAGES) < WT_AT) { __nanosleep(1000); spin_guard(++it); }
                while (true) {
#pragma unroll
                    for (int i = 0; i < 4; ++i) {
                        x[i] = make_uint4(0u, 0u, 0xff7ffffeu | par, 0xff7fffffu);
                        ld_relaxed4_if(x[i], xp + 64 * i, 32 * i + lane < NS);
                    }
                    if (!__any_sync(0xffffffffu, ((x[0].z ^ par) | (x[1].z ^ par) | (x[2].z ^ par) | (x[3].z ^ par)) & 1u)) break;
                    if (real == 1) __nanosleep(1000);
                    spin_guard(++it);
                }
#pragma unroll
                for (int i = 0; i < 4; ++i) x[i].z &= ~1u;
                const float Xa = warp_max(fmaxf(fmaxf(__uint_as_float(x[0].z), __uint_as_float(x[1].z)), fmaxf(__uint_as_float(x[2].z), __uint_as_float(x[3].z))));
                const float Xb = warp_max(fmaxf(fmaxf(__uint_as_float(x[0].w), __uint_as_float(x[1].w)), fmaxf(__uint_as_float(x[2].w), __uint_as_float(x[3].w))));
#pragma unroll
                for (int i = 0; i < 4; ++i) {
                    const uint32_t w2 = pack2(ex2(__uint_as_float(x[i].z) - Xa), ex2(__uint_as_float(x[i].w) - Xb));
                    sts16(SM_FW + (32 * i + lane) * 2, w2); sts16(SM_FW + 272 + (32 * i + lane) * 2, w2 >> 16);
                    stsf2(SM_FX + (32 * i + lane) * 8, __uint_as_float(x[i].z | par), __uint_as_float(x[i].w));
                }
                __syncwarp();
                el_arrive(BAR_WT);
            }
            const uint32_t valid = real && 32 * fw + lane < NS;
            const uint4* lp = scl + (n0 * 128 + min(32 * fw + lane, NS - 1)) * 2;
            uint32_t wa[4];
            sched_fence(sink);
            if (fw) bar_sync(7, 128);
            else mbar_wait_u(real ? BAR_WT : BAR_EP, real ? ~real & 1 : 0);
            {
                const float2 x = ldsf2(SM_FW + (g & 1) * 272 + fw * 64 + j * 8), y = ldsf2(SM_FW + (g & 1) * 272 + fw * 64 + 32 + j * 8);
                wa[0] = __float_as_uint(x.x); wa[1] = __float_as_uint(x.y); wa[2] = __float_as_uint(y.x); wa[3] = __float_as_uint(y.y);
            }
            uint32_t av = lds32(SM_FW + (g & 1) * 272 + (src & ~(CL - 1)) * 2 + j * 4);
            float2 m = ldsf2(SM_FX + ft * 8);
            const uint32_t fin = lds32(SM_EP + 12), buf = real ? fin & ~255u : SB, t0 = (now_ns() - 100000u) & ~1u;
            const float2 ts = ldsf2(SM_FLAG + 8);
            const float nspc = fminf(__fdividef((float)(t0 + 100000u - __float_as_uint(ts.x)), (float)(clk32() - __float_as_uint(ts.y))), 2.f);
            const uint32_t llag = t0 + MEMNS + f2uv(nspc * LLAG);
            uint32_t ldst = buf + ft * 32 + (lane & 4) * 4;
            mbar_wait_u(real ? BAR_EMPTY + (fin >> 4 & 14u) * 4 : BAR_EP, real ? fin >> 4 & 1u : 0u);
            sink128_if(ldst, 0u, real && !valid);
            uint32_t lsum = SM_FIN + 32 + (lane == 5) * 16 + fw * 4, lsrc = SM_FIN + 32 + (j >> 1) * 16, vsrc = SM_A + (lane & 7) * 832 + fw * 192 + (((lane >> 3) ^ (lane >> 1 & 3)) << 4), vb = real ? BAR_V : BAR_EP;
            uint32_t id = 0x3210 + lds32(SM_EP + 4), chk = valid ? ~0u : 0u, wl = lane == 0 || lane == 5;
            uint32_t wr = real && (g & 1) == (j >> 1) ? g >> 1 : 3;
            __nv_bfloat16* op = out + (n0 + (j >> 1) * 8) * CH + 48 * fw + 8 * (j & 1) + 16 * (g >> 1);
            asm volatile("" : "+l"(lp), "+l"(op), "+r"(ldst), "+r"(lsum), "+r"(lsrc), "+r"(vsrc), "+r"(vb), "+r"(chk), "+r"(wl), "+r"(wr), "+r"(id), "+r"(av));
            sched_fence(sink);
            if (real == 1) bar_sync(11, 256);
            const uint32_t tlast = __reduce_max_sync(0xffffffffu, (collect(lp + 8 * 128 * 2, par, real != 0) - t0) & chk);
            if (real == 1) bar_sync(12, 256);
            fetch_at(chk, tlast + llag, ldst, lp, id);
            mbar_wait_u(vb, 0);
            float cv[6][4];
            while (true) {
                uint32_t l[4], b[4], bv[3][4];
                asm volatile("cp.async.wait_all;" ::: "memory");
                __syncwarp();
                ldsm4t(ldst, b);
                lds128(ldst, l);
#pragma unroll
                for (int u = 0; u < 3; ++u) ldsm4t(vsrc + u * 64, bv[u]);
                float c[4];
                mma_sp(c, wa, b);
                uint32_t again, moved;
                {
                    const uint32_t x = (l[2] ^ __float_as_uint(m.x)) & chk;
                    asm volatile("{\n.reg .pred p, q;\nsetp.ne.u32 p, %2, 0;\nsetp.ne.u32 q, %3, 0;\nvote.sync.ballot.b32 %0, p, -1;\nvote.sync.ballot.b32 %1, q, -1;\n}"
                                 : "=r"(again), "=r"(moved) : "r"(x & 1u), "r"(x | ((l[3] ^ __float_as_uint(m.y)) & chk)));
                }
#pragma unroll
                for (int u = 0; u < 6; ++u) {
                    cv[u][0] = cv[u][1] = cv[u][2] = cv[u][3] = 0.f;
                    mma16816(cv[u], av, 0u, 0u, av, bv[u >> 1][2 * (u & 1)], bv[u >> 1][2 * (u & 1) + 1]);
                }
                const float L = (c[0] + c[2]) + (c[1] + c[3]);
                asm volatile("{\n.reg .pred p;\nsetp.ne.u32 p, %2, 0;\n@p st.shared.f32 [%0], %1;\n}" ::"r"(lsum), "f"(moved || !real ? -1.f : fabsf(L)), "r"(wl) : "memory");
                if (!again) break;
                __syncwarp();
                asm volatile("{\n.reg .pred p;\nsetp.ne.u32 p, %2, 0;\n@p cp.async.cg.shared.global [%0], [%1], 16;\n}" ::"r"(ldst), "l"(lp), "r"(chk) : "memory");
                spin_guard(++it);
            }
            bar_sync(13, 128);
            uint32_t d[4];
            lds128(lsrc, d);
            float r[8];
#pragma unroll
            for (int i = 0; i < 8; ++i) r[i] = wr == 0 ? cv[i >> 2][i & 3] : wr == 1 ? cv[2 + (i >> 2)][i & 3] : cv[4 + (i >> 2)][i & 3];
            asm volatile("{\n.reg .pred p;\nsetp.eq.u32 p, %2, 0;\n@p st.global.v2.u32 [%0], {%1, %2};\n}" ::"l"(&sc->epoch), "r"(epoch), "r"(src | fw | lane | !real) : "memory");
            float inv;
            asm volatile("rcp.approx.ftz.f32 %0, %1;" : "=f"(inv) : "f"(sum4(d)));
            const uint32_t redo = (d[0] | d[1] | d[2] | d[3]) >> 31;
            red_if(op, pack2(r[0] * inv, r[1] * inv), pack2(r[2] * inv, r[3] * inv), pack2(r[4] * inv, r[5] * inv), pack2(r[6] * inv, r[7] * inv), !redo && wr < 3);
            if (real && !redo) return;
            sink_if(SM_EP + 8, sink, lds32(SM_EP + 4));
            bar_sync(9, 128);
            spin_guard(real);
        }
        }
    }
}

typedef CUresult (*EncodeFn)(CUtensorMap*, CUtensorMapDataType, cuuint32_t, void*, const cuuint64_t*, const cuuint64_t*,
                             const cuuint32_t*, const cuuint32_t*, CUtensorMapInterleave, CUtensorMapSwizzle,
                             CUtensorMapL2promotion, CUtensorMapFloatOOBfill);

}

extern "C" void kernel_launch(void* const* d_in, const int* in_sizes, int n_in, void* d_out, int out_size) {
    (void)in_sizes; (void)n_in; (void)out_size;
    static EncodeFn enc = nullptr;
    static int grid = 0;
    static Scratch* scratch = nullptr;
    if (!enc) {
        cudaDriverEntryPointQueryResult qr;
        cudaGetDriverEntryPoint("cuTensorMapEncodeTiled", (void**)&enc, cudaEnableDefault, &qr);
        cudaGetSymbolAddress((void**)&scratch, g_s);
        int dev = 0, sms = 0;
        cudaGetDevice(&dev);
        cudaDeviceGetAttribute(&sms, cudaDevAttrMultiProcessorCount, dev);
        (void)sms;
        cudaFuncSetAttribute(fused_kernel, cudaFuncAttributeMaxDynamicSharedMemorySize, SM_TOTAL);
        cudaLaunchConfig_t cfg = {};
        cfg.gridDim = dim3(MAXS); cfg.blockDim = dim3(384); cfg.dynamicSmemBytes = SM_TOTAL;
        cudaLaunchAttribute at[1]; at[0].id = cudaLaunchAttributeClusterDimension; at[0].val.clusterDim.x = CL; at[0].val.clusterDim.y = 1; at[0].val.clusterDim.z = 1;
        cfg.attrs = at; cfg.numAttrs = 1;
        int ncl = 0;
        cudaOccupancyMaxActiveClusters(&ncl, fused_kernel, &cfg);
        grid = (ncl < MAXS / CL ? ncl : MAXS / CL) * CL;
    }
    CUtensorMap tm0, tm1, tmq, tmk, tmv, tmo;
    {
        cuuint64_t gd[3] = {64, 1536, 512}; cuuint64_t gs[2] = {128, 196608};
        cuuint32_t bd[3] = {64, 96, 2}; cuuint32_t es[3] = {1, 1, 1};
        enc(&tm0, CU_TENSOR_MAP_DATA_TYPE_BFLOAT16, 3, d_in[1], gd, gs, bd, es, CU_TENSOR_MAP_INTERLEAVE_NONE,
            CU_TENSOR_MAP_SWIZZLE_128B, CU_TENSOR_MAP_L2_PROMOTION_L2_64B, CU_TENSOR_MAP_FLOAT_OOB_FILL_NONE);
    }
    auto map2d = [&](CUtensorMap* tm, void* p, cuuint64_t cols, cuuint64_t rows, cuuint32_t bc, cuuint32_t br, CUtensorMapSwizzle sw) {
        cuuint64_t gd[2] = {cols, rows}; cuuint64_t gs[1] = {cols * 2};
        cuuint32_t bd[2] = {bc, br}; cuuint32_t es[2] = {1, 1};
        enc(tm, CU_TENSOR_MAP_DATA_TYPE_BFLOAT16, 2, p, gd, gs, bd, es, CU_TENSOR_MAP_INTERLEAVE_NONE,
            sw, CU_TENSOR_MAP_L2_PROMOTION_L2_64B, CU_TENSOR_MAP_FLOAT_OOB_FILL_NONE);
    };
    map2d(&tm1, d_in[2], 64, 196608, 64, 48, CU_TENSOR_MAP_SWIZZLE_128B);
    map2d(&tmq, d_in[3], 64, 576, 64, 192, CU_TENSOR_MAP_SWIZZLE_128B);
    map2d(&tmk, d_in[4], 64, 576, 64, 48, CU_TENSOR_MAP_SWIZZLE_128B);
    map2d(&tmv, d_in[5], 64, 576, 64, 192, CU_TENSOR_MAP_SWIZZLE_128B);
    map2d(&tmo, d_in[6], 192, 192, 16, 192, CU_TENSOR_MAP_SWIZZLE_NONE);
    fused_kernel<<<grid, 384, SM_TOTAL>>>((uint64_t)scratch | (grid - 1), (const __nv_bfloat16*)d_in[0], (const char*)d_in[1], (const char*)d_in[2],
                                          (const char*)d_in[3], (const char*)d_in[4], tm0, tm1, tmq, tmk, tmv, tmo, (__nv_bfloat16*)d_out, scratch->L);
}
```

```cpp
#include <cuda_runtime.h>
#include <cuda.h>
#include <cuda_bf16.h>
#include <stdint.h>

namespace {

constexpr int CH = 192;
constexpr int NTILES = 4096;
constexpr int STAGES = 7;
constexpr int STAGE_BYTES = 30720;
constexpr int NSERV = 12;
constexpr int CL = 8;
constexpr int MAXS = 128;
constexpr float LN_EPS = 1e-5f;
constexpr float EPS2 = LN_EPS * CH * CH;
constexpr float RESCALE_TH = 60.0f;
#define NSTATIC 6
#define JOIN_N 3
static_assert(NSTATIC >= JOIN_N + 3, "a service CTA starts with two static tiles and requests its first ticket with the third one");
#define ORDER_AT 6
#define CHECKPOINT 10
#define WSTAG 15
#define MX_AT 9
#define WT_AT (MX_AT + 6)
#define PAUSE 12
#define D_END 1160
#define END_X 240
#define MID_D 675
#define MID_FROM 16
#define QK_AFTER 3
#define MEMNS 164
#define LLAG 950
#define REL_Z 18
template <int N> __device__ __forceinline__ void pad() { if constexpr (N > 0) { asm volatile("pmevent 1;"); pad<N - 1>(); } }
constexpr unsigned SPIN_LIMIT = 1u << 22;
constexpr uint64_t EVICT_FIRST = 0x12F0000000000000ull;

constexpr uint32_t K_SB = 1024;
constexpr uint32_t K_SM_P = K_SB + STAGES * STAGE_BYTES;
constexpr uint32_t K_SM_A = K_SM_P + 4096;
constexpr uint32_t K_SM_XA = K_SB + (STAGES - 1) * STAGE_BYTES;
constexpr uint32_t K_SM_MX = K_SM_A + 6656;
constexpr uint32_t K_SM_UL = K_SM_MX + 256;
constexpr uint32_t K_SM_AL = K_SM_UL + 512;
constexpr uint32_t K_SM_FIN = K_SM_AL + 128;
constexpr uint32_t K_SM_OW = K_SM_FIN + 64;
constexpr uint32_t K_SM_FW = K_SM_OW + 128;
constexpr uint32_t K_SM_ZERO = K_SM_FW + 768;
constexpr uint32_t K_SM_EP = K_SM_ZERO + 256;
constexpr uint32_t K_SM_FLAG = K_SM_EP + 16;
constexpr uint32_t K_BAR_FULL = K_SM_FLAG + 16, K_BAR_EMPTY = K_BAR_FULL + 8 * STAGES, K_BAR_W = K_BAR_EMPTY + 8 * STAGES;
constexpr uint32_t K_BAR_EP = K_BAR_W + 8;
constexpr uint32_t K_BAR_WT = K_BAR_EP + 8;
constexpr uint32_t K_BAR_V = K_BAR_WT + 8;
constexpr uint32_t K_BAR_JOB = K_BAR_V + 8;
constexpr uint32_t K_SM_INFO = K_BAR_JOB + 8 * 5;
constexpr uint32_t K_SM_TS = K_SM_INFO + 4 * STAGES + 4;
constexpr int SM_TOTAL = K_SM_TS - K_SB;
constexpr uint32_t K_SM_WQ = K_SB, K_SM_WK = K_SM_WQ + CH * CH * 2, K_SM_Q = K_SM_WK + 16 * CH * 2, K_SM_RED = K_SM_Q + 16 * CH * 2;
constexpr uint32_t K_SM_WV = K_SM_RED + 12288, K_SM_WO = K_SM_WV + CH * CH * 2;

#define SB (cb + K_SB)
#define SM_P (cb + K_SM_P)
#define SM_A (cb + K_SM_A)
#define SM_XA (cb + K_SM_XA)
#define SM_MX (cb + K_SM_MX)
#define SM_UL (cb + K_SM_UL)
#define SM_AL (cb + K_SM_AL)
#define SM_FIN (cb + K_SM_FIN)
#define SM_OW (cb + K_SM_OW)
#define SM_FW (cb + K_SM_FW)
#define SM_ZERO (cb + K_SM_ZERO)
#define SM_EP (cb + K_SM_EP)
#define SM_FLAG (cb + K_SM_FLAG)
#define BAR_FULL (cb + K_BAR_FULL)
#define BAR_EMPTY (cb + K_BAR_EMPTY)
#define BAR_W (cb + K_BAR_W)
#define BAR_EP (cb + K_BAR_EP)
#define BAR_WT (cb + K_BAR_WT)
#define BAR_V (cb + K_BAR_V)
#define BAR_JOB (cb + K_BAR_JOB)
#define SM_INFO (cb + K_SM_INFO)
#define SM_TS (cb + K_SM_TS)
#define SM_WQ (cb + K_SM_WQ)
#define SM_WK (cb + K_SM_WK)
#define SM_Q (cb + K_SM_Q)
#define SM_RED (cb + K_SM_RED)
#define SM_WV (cb + K_SM_WV)
#define SM_WO (cb + K_SM_WO)

struct __align__(128) Scratch {
    unsigned epoch, ctr, pad[30];
    unsigned flagW[128];
    uint4 qk[12 * 32];
    uint32_t wvo[3 * 4 * 12 * 128];
    uint4 M[8 * 128 * 2];
    uint4 L[8 * 128 * 2];
    uint4 T[8 * 128 * 2];
    uint4 A[8 * 64];
};
__device__ Scratch g_s;

__device__ __forceinline__ void spin_guard(unsigned it) {
    asm volatile("{\n.reg .pred p;\n.reg .b64 z;\nsetp.gt.u32 p, %0, %1;\nmov.b64 z, 0;\n@p st.global.u32 [z], %0;\n}" ::"r"(it), "n"(SPIN_LIMIT));
}
__device__ __forceinline__ uint32_t smem_u32(const void* p) { return (uint32_t)__cvta_generic_to_shared(p); }
__device__ __forceinline__ void mbar_init(uint32_t bar, int cnt) { asm volatile("mbarrier.init.shared::cta.b64 [%0], %1;" ::"r"(bar), "r"(cnt) : "memory"); }
__device__ __forceinline__ void mbar_expect_tx(uint32_t bar, uint32_t bytes) { asm volatile("mbarrier.arrive.expect_tx.shared::cta.b64 _, [%0], %1;" ::"r"(bar), "r"(bytes) : "memory"); }
__device__ __forceinline__ void mbar_arrive_if(uint32_t bar, uint32_t cond) {
    asm volatile("{\n.reg .pred p;\nsetp.ne.u32 p, %1, 0;\n@p mbarrier.arrive.shared::cta.b64 _, [%0];\n}" ::"r"(bar), "r"(cond) : "memory");
}
__device__ __forceinline__ void mbar_wait(uint32_t bar, uint32_t parity) {
    asm volatile("{\n.reg .pred p;\n.reg .u32 c;\n.reg .b64 z;\nmov.u32 c, 0;\nmov.b64 z, 0;\nbra.uni T_%=;\n"
                 "W_%=:\nadd.u32 c, c, 1;\nsetp.gt.u32 p, c, %2;\n@p st.global.u32 [z], c;\n"
                 "T_%=:\nmbarrier.try_wait.parity.shared::cta.b64 p, [%0], %1;\n@!p bra W_%=;\n}"
                 ::"r"(bar), "r"(parity), "n"(SPIN_LIMIT / 4) : "memory");
}
__device__ __forceinline__ void mbar_wait_u(uint32_t bar, uint32_t parity) {
    asm volatile("{\n.reg .pred p;\n.reg .u32 c;\n.reg .b64 z;\nmov.u32 c, 0;\nmov.b64 z, 0;\nbra.uni T_%=;\n"
                 "W_%=:\nadd.u32 c, c, 1;\nsetp.gt.u32 p, c, %2;\n@p st.global.u32 [z], c;\n"
                 "T_%=:\nmbarrier.try_wait.parity.shared::cta.b64 p, [%0], %1;\n@!p bra.uni W_%=;\n}"
                 ::"r"(bar), "r"(parity), "n"(SPIN_LIMIT / 4) : "memory");
}
__device__ __forceinline__ bool mbar_test(uint32_t bar, uint32_t parity) {
    uint32_t ok;
    asm volatile("{\n.reg .pred p;\nmbarrier.test_wait.parity.shared::cta.b64 p, [%1], %2;\nselp.u32 %0, 1, 0, p;\n}" : "=r"(ok) : "r"(bar), "r"(parity) : "memory");
    return ok != 0;
}
__device__ __forceinline__ void tma3d(uint32_t dst, const CUtensorMap* tm, int c0, int c1, int c2, uint32_t bar) {
    asm volatile("cp.async.bulk.tensor.3d.shared::cluster.global.mbarrier::complete_tx::bytes.L2::cache_hint [%0], [%1, {%3, %4, %5}], [%2], %6;"
                 ::"r"(dst), "l"(tm), "r"(bar), "r"(c0), "r"(c1), "r"(c2), "l"(EVICT_FIRST) : "memory");
}
__device__ __forceinline__ void tma2d(uint32_t dst, const CUtensorMap* tm, int c0, int c1, uint32_t bar) {
    asm volatile("cp.async.bulk.tensor.2d.shared::cluster.global.mbarrier::complete_tx::bytes.L2::cache_hint [%0], [%1, {%3, %4}], [%2], %5;"
                 ::"r"(dst), "l"(tm), "r"(bar), "r"(c0), "r"(c1), "l"(EVICT_FIRST) : "memory");
}
__device__ __forceinline__ void tma2dn(uint32_t dst, const CUtensorMap* tm, int c0, int c1, uint32_t bar) {
    asm volatile("cp.async.bulk.tensor.2d.shared::cluster.global.mbarrier::complete_tx::bytes [%0], [%1, {%3, %4}], [%2];"
                 ::"r"(dst), "l"(tm), "r"(bar), "r"(c0), "r"(c1) : "memory");
}
__device__ __forceinline__ void bulk_g2s(uint32_t dst, const void* src, uint32_t bytes, uint32_t bar) {
    asm volatile("cp.async.bulk.shared::cluster.global.mbarrier::complete_tx::bytes [%0], [%1], %2, [%3];" ::"r"(dst), "l"(src), "r"(bytes), "r"(bar) : "memory");
}
__device__ __forceinline__ void ldsm4(uint32_t a, uint32_t (&r)[4]) {
    asm volatile("ldmatrix.sync.aligned.m8n8.x4.shared.b16 {%0,%1,%2,%3}, [%4];" : "=r"(r[0]), "=r"(r[1]), "=r"(r[2]), "=r"(r[3]) : "r"(a) : "memory");
}
__device__ __forceinline__ void ldsm4t(uint32_t a, uint32_t (&r)[4]) {
    asm volatile("ldmatrix.sync.aligned.m8n8.x4.trans.shared.b16 {%0,%1,%2,%3}, [%4];" : "=r"(r[0]), "=r"(r[1]), "=r"(r[2]), "=r"(r[3]) : "r"(a) : "memory");
}
__device__ __forceinline__ void stsm4(uint32_t a, uint32_t x, uint32_t y, uint32_t z, uint32_t w) {
    asm volatile("stmatrix.sync.aligned.m8n8.x4.shared.b16 [%0], {%1,%2,%3,%4};" ::"r"(a), "r"(x), "r"(y), "r"(z), "r"(w) : "memory");
}
__device__ __forceinline__ void mma16816(float (&d)[4], uint32_t a0, uint32_t a1, uint32_t a2, uint32_t a3, uint32_t b0, uint32_t b1) {
    asm volatile("mma.sync.aligned.m16n8k16.row.col.f32.bf16.bf16.f32 {%0,%1,%2,%3}, {%4,%5,%6,%7}, {%8,%9}, {%0,%1,%2,%3};"
        : "+f"(d[0]), "+f"(d[1]), "+f"(d[2]), "+f"(d[3]) : "r"(a0), "r"(a1), "r"(a2), "r"(a3), "r"(b0), "r"(b1));
}
__device__ __forceinline__ void mma_sp(float (&d)[4], const uint32_t (&a)[4], const uint32_t (&b)[4]) {
    asm volatile("mma.sp::ordered_metadata.sync.aligned.m16n8k32.row.col.f32.bf16.bf16.f32 {%0,%1,%2,%3}, {%4,%5,%6,%7}, {%8,%9,%10,%11}, {%12,%12,%12,%12}, %13, 0x0;"
        : "=f"(d[0]), "=f"(d[1]), "=f"(d[2]), "=f"(d[3])
        : "r"(a[0]), "r"(a[1]), "r"(a[2]), "r"(a[3]), "r"(b[0]), "r"(b[1]), "r"(b[2]), "r"(b[3]), "f"(0.f), "r"(0xEEEE4444u));
}
__device__ __forceinline__ uint32_t badd2v(uint32_t a, uint32_t b) { uint32_t d; asm volatile("add.rn.bf16x2 %0, %1, %2;" : "=r"(d) : "r"(a), "r"(b)); return d; }
__device__ __forceinline__ uint32_t negv(uint32_t a) { uint32_t d; asm volatile("xor.b32 %0, %1, 0x80008000;" : "=r"(d) : "r"(a)); return d; }
__device__ __forceinline__ uint32_t pack2(float lo, float hi) { uint32_t d; asm("cvt.rn.bf16x2.f32 %0, %1, %2;" : "=r"(d) : "f"(hi), "f"(lo)); return d; }
__device__ __forceinline__ float bf_lo(uint32_t v) { return __uint_as_float(v << 16); }
__device__ __forceinline__ float bf_hi(uint32_t v) { return __uint_as_float(v & 0xffff0000u); }
__device__ __forceinline__ float ex2(float x) { float y; asm("ex2.approx.ftz.f32 %0, %1;" : "=f"(y) : "f"(x)); return y; }
__device__ __forceinline__ float rsq(float x) { float y; asm("rsqrt.approx.ftz.f32 %0, %1;" : "=f"(y) : "f"(x)); return y; }
__device__ __forceinline__ void bar_sync(int id, int n) { asm volatile("bar.sync %0, %1;" ::"r"(id), "r"(n) : "memory"); }
__device__ __forceinline__ void bar_arrive(int id, int n) { asm volatile("bar.arrive %0, %1;" ::"r"(id), "r"(n) : "memory"); }
__device__ __forceinline__ unsigned ld_acquire(const unsigned* p) { unsigned v; asm volatile("ld.acquire.gpu.global.u32 %0, [%1];" : "=r"(v) : "l"(p) : "memory"); return v; }
__device__ __forceinline__ void st_release(unsigned* p, unsigned v) { asm volatile("st.release.gpu.global.u32 [%0], %1;" ::"l"(p), "r"(v) : "memory"); }
__device__ __forceinline__ uint4 ld_relaxed4(const uint4* p) {
    uint4 v; asm volatile("ld.relaxed.gpu.global.v4.u32 {%0,%1,%2,%3}, [%4];" : "=r"(v.x), "=r"(v.y), "=r"(v.z), "=r"(v.w) : "l"(p) : "memory"); return v;
}
__device__ __forceinline__ void ld_relaxed4_if(uint4& v, const uint4* p, uint32_t cond) {
    asm volatile("{\n.reg .pred p;\nsetp.ne.u32 p, %5, 0;\n@p ld.relaxed.gpu.global.v4.u32 {%0,%1,%2,%3}, [%4];\n}"
                 : "+r"(v.x), "+r"(v.y), "+r"(v.z), "+r"(v.w) : "l"(p), "r"(cond) : "memory");
}
__device__ __forceinline__ uint32_t collect(const uint4* tp, uint32_t par, uint32_t on) {
    uint32_t t;
    asm volatile("{\n.reg .pred p, q, r;\n.reg .b32 u, c;\n.reg .b64 z;\nmov.b32 c, 0;\nmov.b64 z, 0;\nmov.b32 %0, 0;\nsetp.ne.u32 r, %3, 0;\n"
                 "L_%=:\n@r ld.relaxed.gpu.global.u32 %0, [%1];\nadd.u32 c, c, 1;\nsetp.gt.u32 q, c, %4;\n@q st.global.u32 [z], c;\n"
                 "lop3.b32 u, %0, %2, %3, 0x28;\nsetp.ne.u32 p, u, 0;\nvote.sync.any.pred p, p, -1;\n@p bra.uni L_%=;\n}"
                 : "=&r"(t) : "l"(tp), "r"(par), "r"(on), "n"(SPIN_LIMIT) : "memory");
    return t;
}
__device__ __forceinline__ void load_at(float2& v, uint32_t on, uint32_t tl, const float2* p, uint32_t id) {
    asm volatile("{\n.reg .pred q, r;\n.reg .b32 t0, t1;\n.reg .b64 g;\n"
                 "A_%=:\nmov.u64 g, %%globaltimer;\ncvt.u32.u64 t0, g;\nsub.u32 t0, t0, %3;\nsetp.lt.s32 q, t0, 0;\n@q bra.uni A_%=;\n"
                 "prmt.b32 t1, %2, t0, %5;\n"
                 "prmt.b32 t1, t1, t1, %5;\n"
                 "prmt.b32 t1, t1, t1, %5;\n"
                 "setp.ne.u32 r, t1, 0;\n@r ld.relaxed.gpu.global.v2.f32 {%0,%1}, [%4];\n}"
                 : "+f"(v.x), "+f"(v.y) : "r"(on), "r"(tl), "l"(p), "r"(id) : "memory");
}
__device__ __forceinline__ void st_async_if(uint32_t dst, uint32_t a, uint32_t b, uint32_t c, uint32_t d, uint32_t bar, uint32_t cond) {
    asm volatile("{\n.reg .pred p;\nsetp.ne.u32 p, %6, 0;\n@p st.async.weak.shared::cluster.mbarrier::complete_tx::bytes.v4.b32 [%0], {%1,%2,%3,%4}, [%5];\n}"
                 ::"r"(dst), "r"(a), "r"(b), "r"(c), "r"(d), "r"(bar), "r"(cond) : "memory");
}
__device__ __forceinline__ void red_if(__nv_bfloat16* p, uint32_t a, uint32_t b, uint32_t c, uint32_t d, bool cond) {
    asm volatile("{\n.reg .pred p;\nsetp.ne.u32 p, %5, 0;\n@p red.global.add.noftz.v4.bf16x2 [%0], {%1,%2,%3,%4};\n}"
                 ::"l"(p), "r"(a), "r"(b), "r"(c), "r"(d), "r"((uint32_t)cond) : "memory");
}
__device__ __forceinline__ uint32_t mapa(uint32_t a, uint32_t rank) { uint32_t d; asm volatile("mapa.shared::cluster.u32 %0, %1, %2;" : "=r"(d) : "r"(a), "r"(rank)); return d; }
__device__ __forceinline__ uint32_t f2uv(float x) { uint32_t r; asm volatile("cvt.rzi.u32.f32 %0, %1;" : "=r"(r) : "f"(x)); return r; }
__device__ __forceinline__ void sts16(uint32_t a, uint32_t x) { asm volatile("{\n.reg .b16 h;\ncvt.u16.u32 h, %1;\nst.shared.u16 [%0], h;\n}" ::"r"(a), "r"(x) : "memory"); }
__device__ __forceinline__ void st_v4(uint4* p, uint32_t a, uint32_t b, uint32_t c, uint32_t d) {
    asm volatile("st.relaxed.gpu.global.v4.u32 [%0], {%1,%2,%3,%4};" ::"l"(p), "r"(a), "r"(b), "r"(c), "r"(d) : "memory");
}
__device__ __forceinline__ void st_v4_if(uint4* p, uint32_t a, uint32_t b, uint32_t c, uint32_t d, bool cond) {
    asm volatile("{\n.reg .pred p;\nsetp.ne.u32 p, %5, 0;\n@p st.relaxed.gpu.global.v4.u32 [%0], {%1,%2,%3,%4};\n}"
                 ::"l"(p), "r"(a), "r"(b), "r"(c), "r"(d), "r"((uint32_t)cond) : "memory");
}
__device__ __forceinline__ uint32_t pack2t(float lo, float hi, uint32_t par) {
    return (__byte_perm(__float_as_uint(lo) + ((par ^ 1u) << 16), pack2(0.f, hi), 0x7632) & ~1u) | par;
}
__device__ __forceinline__ void lds128(uint32_t a, uint32_t (&r)[4]) {
    asm volatile("ld.shared.v4.u32 {%0,%1,%2,%3}, [%4];" : "=r"(r[0]), "=r"(r[1]), "=r"(r[2]), "=r"(r[3]) : "r"(a) : "memory");
}
__device__ __forceinline__ float sum4(const uint32_t (&r)[4]) {
    return (__uint_as_float(r[0]) + __uint_as_float(r[1])) + (__uint_as_float(r[2]) + __uint_as_float(r[3]));
}
__device__ __forceinline__ void sts32(uint32_t a, uint32_t x) { asm volatile("st.shared.u32 [%0], %1;" ::"r"(a), "r"(x) : "memory"); }
__device__ __forceinline__ void stsf(uint32_t a, float x) { asm volatile("st.shared.f32 [%0], %1;" ::"r"(a), "f"(x) : "memory"); }
__device__ __forceinline__ void stsf2(uint32_t a, float x, float y) { asm volatile("st.shared.v2.f32 [%0], {%1,%2};" ::"r"(a), "f"(x), "f"(y) : "memory"); }
__device__ __forceinline__ float ldsf(uint32_t a) { float v; asm volatile("ld.shared.f32 %0, [%1];" : "=f"(v) : "r"(a) : "memory"); return v; }
__device__ __forceinline__ float2 ldsf2(uint32_t a) { float2 v; asm volatile("ld.shared.v2.f32 {%0,%1}, [%2];" : "=f"(v.x), "=f"(v.y) : "r"(a) : "memory"); return v; }
__device__ __forceinline__ uint32_t lds32(uint32_t a) { uint32_t v; asm volatile("ld.shared.u32 %0, [%1];" : "=r"(v) : "r"(a) : "memory"); return v; }
__device__ __forceinline__ uint32_t ldsv32(uint32_t a) { uint32_t v; asm volatile("ld.volatile.shared.u32 %0, [%1];" : "=r"(v) : "r"(a) : "memory"); return v; }
__device__ __forceinline__ float warp_max(float x) {
    int k = __float_as_int(x);
    k = __reduce_max_sync(0xffffffffu, k ^ ((k >> 31) & 0x7fffffff));
    return __int_as_float(k ^ ((k >> 31) & 0x7fffffff));
}
__device__ __forceinline__ uint32_t now_ns() { uint32_t t; asm volatile("mov.u32 %0, %globaltimer_lo;" : "=r"(t) :: "memory"); return t; }
__device__ __forceinline__ uint32_t clk32() { uint32_t t; asm volatile("mov.u32 %0, %clock;" : "=r"(t) :: "memory"); return t; }
__device__ __forceinline__ void sched_fence(uint32_t& sink) { uint64_t t; asm volatile("mov.u64 %0, %clock64;" : "=l"(t) :: "memory"); sink ^= (uint32_t)(t >> 32); }
__device__ __forceinline__ void sink_if(uint32_t addr, uint32_t sink, uint32_t cond) {
    asm volatile("{\n.reg .pred p;\nsetp.ne.u32 p, %2, 0;\n@p st.shared.u32 [%0], %1;\n}" ::"r"(addr), "r"(sink), "r"(cond) : "memory");
}
__device__ __forceinline__ uint32_t opaque(uint32_t v, int lane) { return __shfl_sync(0xffffffffu, v, lane); }

__device__ __forceinline__ void el_arrive(uint32_t bar) {
    asm volatile("{\n.reg .pred p;\nelect.sync _|p, -1;\n@p mbarrier.arrive.shared::cta.b64 _, [%0];\n}" ::"r"(bar) : "memory");
}
__device__ __forceinline__ void el_expect_tx(uint32_t bar, uint32_t bytes) {
    asm volatile("{\n.reg .pred p;\nelect.sync _|p, -1;\n@p mbarrier.arrive.expect_tx.shared::cta.b64 _, [%0], %1;\n}" ::"r"(bar), "r"(bytes) : "memory");
}
__device__ __forceinline__ void el_tile(uint32_t cb, int s, int t, const CUtensorMap* tm0, const CUtensorMap* tm1) {
    asm volatile("{\n.reg .pred p;\nelect.sync _|p, -1;\n"
                 "@p cp.async.bulk.tensor.3d.shared::cluster.global.mbarrier::complete_tx::bytes.L2::cache_hint [%0], [%1, {%9, %4, %5}], [%3], %7;\n"
                 "@p cp.async.bulk.tensor.2d.shared::cluster.global.mbarrier::complete_tx::bytes.L2::cache_hint [%8], [%2, {%9, %6}], [%3], %7;\n}"
                 ::"r"(SB + s * STAGE_BYTES), "l"(tm0), "l"(tm1), "r"(BAR_FULL + 8 * s), "r"((t & 15) * 96), "r"((t >> 4) * 2), "r"(t * 48),
                   "l"(EVICT_FIRST), "r"(SB + s * STAGE_BYTES + 24576), "r"(0) : "memory");
}
__device__ __forceinline__ void el_bulk(uint32_t dst, const void* src, uint32_t bytes, uint32_t bar) {
    asm volatile("{\n.reg .pred p;\nelect.sync _|p, -1;\n"
                 "@p cp.async.bulk.shared::cluster.global.mbarrier::complete_tx::bytes [%0], [%1], %2, [%3];\n}" ::"r"(dst), "l"(src), "r"(bytes), "r"(bar) : "memory");
}
__device__ __forceinline__ void issue_tile(uint32_t cb, int s, int t, const CUtensorMap* tm0, const CUtensorMap* tm1) {
    const uint32_t bar = BAR_FULL + 8 * s;
    mbar_expect_tx(bar, STAGE_BYTES);
    tma3d(SB + s * STAGE_BYTES, tm0, 0, (t & 15) * 96, (t >> 4) * 2, bar);
    tma2d(SB + s * STAGE_BYTES + 24576, tm1, 0, t * 48, bar);
}

__global__ void __cluster_dims__(CL, 1, 1) __launch_bounds__(384, 1)
fused_kernel(uint64_t scn  , const __nv_bfloat16* __restrict__ q,
             const char* f0, const char* f1, const char* wq, const char* wk,
             const __grid_constant__ CUtensorMap tm0, const __grid_constant__ CUtensorMap tm1,
             const __grid_constant__ CUtensorMap tmq, const __grid_constant__ CUtensorMap tmk,
             const __grid_constant__ CUtensorMap tmv, const __grid_constant__ CUtensorMap tmo,
             __nv_bfloat16* __restrict__ out, const uint4* scl) {
    extern __shared__ __align__(1024) char smem_raw[];
    const int tid = threadIdx.x, warp = tid >> 5, lane = tid & 31;
    const int bid = blockIdx.x, e0 = bid - NSERV;
    const uint32_t cb0 = smem_u32(smem_raw) - K_SB;

    Scratch* const sc = reinterpret_cast<Scratch*>(scn & ~(uint64_t)127);
    [[maybe_unused]] const uint32_t cb = cb0;
    const int NS = ((int)scn & 127) + 1;
    const int NE = NS - NSERV, src = bid;
    int ticket = 0;
    asm volatile("{\n.reg .pred p, s;\n.reg .b32 a, b;\n.reg .b64 x, y;\nsetp.ne.u32 p, %8, 256;\nsetp.lt.s32 s, %9, 0;\n@p bra N_%=;\n@s bra.uni V_%=;\n"
                 "and.b32 a, %9, -16;\nadd.u32 a, a, %9;\nmad.wide.u32 x, a, 12288, %1;\nmad.wide.u32 y, %9, 6144, %2;\n"
                 "cp.async.bulk.prefetch.L2.global.L2::cache_hint [x], 12288, %6;\ncp.async.bulk.prefetch.L2.global.L2::cache_hint [y], 6144, %6;\n"
                 "cp.async.bulk.prefetch.L2.global.L2::cache_hint [x+196608], 12288, %6;\n"
                 "bra E_%=;\n"
                 "V_%=:\nadd.u32 b, %9, %10;\nmad.wide.u32 x, b, 512, %5;\ncp.async.bulk.prefetch.L2.global [x], 512;\n"
                 "mad.wide.u32 x, b, 6144, %4;\ncp.async.bulk.prefetch.L2.global [x], 6144;\n"
                 "mad.wide.u32 y, b, 6144, %3;\ncp.async.bulk.prefetch.L2.global [y], 6144;\nbra E_%=;\n"
                 "N_%=:\nsetp.eq.u32 p, %8, 288;\n@p ld.relaxed.gpu.global.u32 %0, [%7];\nE_%=:\n}"
                 : "+r"(ticket) : "l"(f0), "l"(f1), "l"(wq), "l"(wk), "l"(q), "l"(EVICT_FIRST), "l"(&sc->epoch), "r"(tid), "r"(e0), "n"(NSERV) : "memory");
    if (tid == 320) {
        mbar_init(BAR_FULL, 2);
        if (e0 >= 0) {
            issue_tile(cb, 0, e0, &tm0, &tm1);
        } else {
#pragma unroll
            for (int i = 0; i < 5; ++i) mbar_init(BAR_JOB + 8 * i, 1);
            mbar_expect_tx(BAR_JOB, 32 * CH * 2);
            bulk_g2s(SM_Q, q, 16 * CH * 2, BAR_JOB);
            tma2dn(SM_WK, &tmk, 0, bid * 48, BAR_JOB);
#pragma unroll
            for (int c = 0; c < 3; ++c) {
                mbar_expect_tx(BAR_JOB + 8 + 8 * c, 64 * CH * 2);
                tma2dn(SM_WQ + c * 64 * CH * 2, &tmq, 0, c * 192, BAR_JOB + 8 + 8 * c);
            }
        }
    } else if (tid == 0) {
#pragma unroll
        for (int i = 1; i < 2 * STAGES + 4; ++i)
            mbar_init(BAR_FULL + 8 * i, i < STAGES ? 2 : 1);
        mbar_expect_tx(BAR_V, CL * 768);
        asm volatile("fence.mbarrier_init.release.cluster;" ::: "memory");
    } else if (warp == 1) {
        stsf2(SM_ZERO + lane * 8, 0.f, 0.f);
        if (lane < 4) stsf2(SM_EP + lane * 8, 0.f, 0.f);
        if (lane <= STAGES) sts32(SM_INFO + 4 * lane, lane == STAGES - 1);
        spin_guard((smem_u32(smem_raw) & 0xffffffu) == K_SB ? 0u : ~0u);
    }
    __syncthreads();
    if (warp != 11) asm volatile("barrier.cluster.arrive.relaxed.aligned;" ::: "memory");

    const int g = lane >> 2, j = lane & 3, m4 = lane >> 3, r8 = lane & 7;

    if (e0 < 0) {
        if (tid == 320) {
            mbar_expect_tx(BAR_JOB + 32, (CH + 16) * CH * 2);
            tma2dn(SM_WO, &tmo, bid * 16, 0, BAR_JOB + 32);
#pragma unroll
            for (int c = 0; c < 3; ++c) tma2dn(SM_WV + c * 64 * CH * 2, &tmv, 0, c * 192, BAR_JOB + 32);
        }
        if (tid == 288) sts32(SM_EP, ticket + 1);
        if (warp == 9) st_v4(&sc->qk[bid * 32 + lane], __shfl_sync(0xffffffffu, ticket, 0), 0u, 0u, 0u);
        st_v4_if(reinterpret_cast<uint4*>(sc->flagW) + bid * 2 + (tid & 1), 0u, 0u, 0u, 0u, tid < 2);
        __syncwarp();
        mbar_wait(BAR_JOB, 0);
        if (warp == 10) {
            uint32_t t[4];
            lds128(SM_Q + bid * 512 + lane * 16, t);
            st_v4(reinterpret_cast<uint4*>(out) + bid * 32 + lane, t[0], t[1], t[2], t[3]);
            st_v4_if(&sc->A[(bid & 7) * 64 + (lane & 7)], 0u, 0u, 0u, 0u, bid < 8 && lane < 8);
        }
        if (warp < 8) {
            const int row = 2 * warp + (lane >> 4), c0 = (lane & 15) * 8;
            float v[3][4];
#pragma unroll
            for (int c = 0; c < 3; ++c) {
                const float2 t = ldsf2(SM_Q + row * 384 + c * 128 + c0);
                v[c][0] = bf_lo(__float_as_uint(t.x)); v[c][1] = bf_hi(__float_as_uint(t.x));
                v[c][2] = bf_lo(__float_as_uint(t.y)); v[c][3] = bf_hi(__float_as_uint(t.y));
            }
            float sum = ((v[0][0] + v[0][1]) + (v[0][2] + v[0][3])) + ((v[1][0] + v[1][1]) + (v[1][2] + v[1][3])) + ((v[2][0] + v[2][1]) + (v[2][2] + v[2][3]));
#pragma unroll
            for (int d = 1; d < 16; d <<= 1) sum += __shfl_xor_sync(0xffffffffu, sum, d);
            const float mean = sum * (1.f / CH);
            float ss[3];
#pragma unroll
            for (int c = 0; c < 3; ++c) {
#pragma unroll
                for (int e = 0; e < 4; ++e) v[c][e] -= mean;
                ss[c] = fmaf(v[c][0], v[c][0], v[c][1] * v[c][1]) + fmaf(v[c][2], v[c][2], v[c][3] * v[c][3]);
            }
            sum = ss[0] + ss[1] + ss[2];
#pragma unroll
            for (int d = 1; d < 16; d <<= 1) sum += __shfl_xor_sync(0xffffffffu, sum, d);
            const float rstd = rsq(sum * (1.f / CH) + LN_EPS);
#pragma unroll
            for (int c = 0; c < 3; ++c)
                stsf2(SM_A + row * 400 + c * 128 + c0, __uint_as_float(pack2(v[c][0] * rstd, v[c][1] * rstd)), __uint_as_float(pack2(v[c][2] * rstd, v[c][3] * rstd)));
        }
        {
            float d[2][2][4];
#pragma unroll
            for (int c = 0; c < 4; ++c) d[0][0][c] = d[0][1][c] = d[1][0][c] = d[1][1][c] = 0.f;
            uint32_t a[12][4], qa[4];
#pragma unroll
            for (int k = 0; k < 12; ++k) {
                const int r = 3 * ((m4 & 1) * 8 + r8) + (k >> 2);
                ldsm4(SM_WK + r * 128 + ((((k & 3) * 2 + (m4 >> 1)) ^ (r & 7)) << 4), a[k]);
            }
            mbar_wait(BAR_JOB + 8 + 8 * (warp >> 2), 0);
#pragma unroll
            for (int k = 0; k < 12; ++k) {
                uint32_t b[4];
                const int r = 3 * ((m4 >> 1) * 8 + r8) + (k >> 2);
                ldsm4(SM_WQ + warp * 6144 + r * 128 + ((((k & 3) * 2 + (m4 & 1)) ^ (r & 7)) << 4), b);
                mma16816(d[0][k & 1], a[k][0], a[k][1], a[k][2], a[k][3], b[0], b[1]);
                mma16816(d[1][k & 1], a[k][0], a[k][1], a[k][2], a[k][3], b[2], b[3]);
            }
            bar_sync(1, 384);
            ldsm4(SM_A + ((m4 & 1) * 8 + r8) * 400 + (16 * warp + (m4 >> 1) * 8) * 2, qa);
#pragma unroll
            for (int nb = 0; nb < 2; ++nb) {
                uint32_t hi[2], lo[2];
#pragma unroll
                for (int t = 0; t < 2; ++t) {
                    const float v0 = d[t][0][2 * nb] + d[t][1][2 * nb], v1 = d[t][0][2 * nb + 1] + d[t][1][2 * nb + 1];
                    hi[t] = pack2(v0, v1);
                    lo[t] = pack2(v0 - bf_lo(hi[t]), v1 - bf_hi(hi[t]));
                }
                float e[4] = {0.f, 0.f, 0.f, 0.f};
                mma16816(e, qa[0], qa[1], qa[2], qa[3], hi[0], hi[1]);
                mma16816(e, qa[0], qa[1], qa[2], qa[3], lo[0], lo[1]);
                stsm4(SM_RED + (warp * 2 + nb) * 512 + lane * 16, __float_as_uint(e[0]), __float_as_uint(e[1]), __float_as_uint(e[2]), __float_as_uint(e[3]));
            }
            bar_sync(1, 384);
            if (warp == 0) {
                float r[8] = {0.f, 0.f, 0.f, 0.f, 0.f, 0.f, 0.f, 0.f};
#pragma unroll
                for (int u = 0; u < 24; ++u) {
                    uint32_t e[4];
                    ldsm4(SM_RED + u * 512 + lane * 16, e);
#pragma unroll
                    for (int c = 0; c < 4; ++c) r[(u & 1) * 4 + c] += __uint_as_float(e[c]);
                }
                const float qs = 1.4426950408889634f * 13.856406460551018f;
                const uint32_t a0 = pack2t(r[0] * qs, r[1] * qs, lds32(SM_EP) & 1u), a1 = pack2(r[2] * qs, r[3] * qs);
                const uint32_t a2 = pack2(r[4] * qs, r[5] * qs), a3 = pack2(r[6] * qs, r[7] * qs);
                st_v4(&sc->qk[bid * 32 + lane], a0, a1, a2, a3);
            }
        }
        {
            mbar_wait(BAR_JOB + 32, 0);
            float d[2][4] = {{0.f, 0.f, 0.f, 0.f}, {0.f, 0.f, 0.f, 0.f}};
#pragma unroll 1
            for (int k = 0; k < 12; ++k) {
                uint32_t a[4], b[4];
                ldsm4t(SM_WO + (16 * k + (m4 >> 1) * 8 + r8) * 32 + (m4 & 1) * 16, a);
                const int r = 3 * ((m4 >> 1) * 8 + r8) + (k >> 2);
                ldsm4(SM_WV + warp * 6144 + r * 128 + ((((k & 3) * 2 + (m4 & 1)) ^ (r & 7)) << 4), b);
                mma16816(d[0], a[0], a[1], a[2], a[3], b[0], b[1]);
                mma16816(d[1], a[0], a[1], a[2], a[3], b[2], b[3]);
            }
            float s0 = (d[0][0] + d[0][1]) + (d[1][0] + d[1][1]), s1 = (d[0][2] + d[0][3]) + (d[1][2] + d[1][3]);
            s0 += __shfl_xor_sync(0xffffffffu, s0, 1); s1 += __shfl_xor_sync(0xffffffffu, s1, 1);
            s0 += __shfl_xor_sync(0xffffffffu, s0, 2); s1 += __shfl_xor_sync(0xffffffffu, s1, 2);
            if (j == 0) stsf2(SM_FW + (warp * 8 + g) * 8, s0, s1);
            bar_sync(1, 384);
            s0 = s1 = 0.f;
#pragma unroll 1
            for (int u = 0; u < 12; ++u) { const float2 t = ldsf2(SM_FW + (u * 8 + g) * 8); s0 += t.x; s1 += t.y; }
            s0 *= 1.f / CH; s1 *= 1.f / CH;
            const int h = bid / 3, i = (warp + 12 - 3 * h) % 12;
            uint32_t* wp = &sc->wvo[(((i >> 2) * 4 + h) * 12 + (i & 3) * 3 + bid % 3) * 128 + lane];
            wp[0] = pack2(d[0][0] - s0, d[0][1] - s0); wp[32] = pack2(d[1][0] - s0, d[1][1] - s0);
            wp[64] = pack2(d[0][2] - s1, d[0][3] - s1); wp[96] = pack2(d[1][2] - s1, d[1][3] - s1);
            asm volatile("fence.proxy.async;" ::: "memory");
            bar_sync(1, 384);
            if (tid == 0) st_release(&sc->flagW[bid * 8], lds32(SM_EP));
        }
    }

    if (warp < 4) {
        asm volatile("setmaxnreg.inc.sync.aligned.u32 176;");
        const uint32_t cb = opaque(cb0, lane);
        const int w = warp;
        uint32_t oa[6], ob[6];
#pragma unroll
        for (int b = 0; b < 3; ++b) {
            int r = 3 * (8 * w + r8) + b;
            uint32_t o = SB + r * 128 + ((m4 ^ (r & 7)) << 4);
            oa[2 * b] = opaque(o, lane); oa[2 * b + 1] = opaque(o ^ 64u, lane);
            r = 3 * (4 * w + (r8 >> 1)) + b;
            o = SB + 24576 + r * 128 + ((m4 ^ 1 ^ (r & 7)) << 4);
            ob[2 * b] = opaque(o, lane); ob[2 * b + 1] = opaque(o ^ 64u, lane);
        }
        uint32_t one[4][2];
#pragma unroll
        for (int i = 0; i < 4; ++i) {
            one[i][0] = 0x3F803F80u + lds32(SM_ZERO + (lane + 2 * i) * 4); one[i][1] = 0x3F803F80u + lds32(SM_ZERO + (lane + 2 * i + 1) * 4);
        }
        const uint32_t dmask = opaque(j == (g >> 1) ? 0xffff0000u : 0u, lane);
        const float dsel = __uint_as_float(opaque(j == (g >> 1) ? 0x3f800000u : 0u, lane));
        const bool odd = opaque(g & 1, lane) != 0;
        uint32_t first = 0;
        const uint32_t pst = opaque(SM_P + w * 512 + lane * 16, lane);
        const uint32_t lst = opaque(SM_UL + 256 + (j & 1) * 128 + g * 16 + w * 4, lane), loff = opaque(((g * 128 + src) * 2 + (j & 1)) * 16, lane);
        const bool odj = lst & 128;
        uint32_t qk[12][4];
#pragma unroll
        for (int k = 0; k < 12; ++k) qk[k][0] = qk[k][1] = qk[k][2] = qk[k][3] = 0u;
        float R0 = 0.f, R1 = 0.f;
        float m0 = -INFINITY, m1 = -INFINITY, l0 = 0.f, l1 = 0.f;
        int s = STAGES - 1; uint32_t st = (STAGES - 1) * STAGE_BYTES, ph = 1, pbuf = 0;
        uint32_t sink = lds32(SM_ZERO + (lane + 8) * 4), seq = 0;
        mbar_wait(BAR_EP, 0);
#pragma unroll 1
        while (true) {
            mbar_wait(BAR_FULL + 8 * s, ph);
            uint32_t r0[6][4], r1[6][4], f[6][4];
            float S2[2][2][4], T2[2][2][4];
#pragma unroll
            for (int b = 0; b < 2; ++b)
#pragma unroll
                for (int c = 0; c < 4; ++c) { S2[0][b][c] = S2[1][b][c] = 0.f; T2[0][b][c] = T2[1][b][c] = 0.f; }
            uint32_t d0[2][2], d1[2][2];
#pragma unroll
            for (int n = 0; n < 2; ++n) { ldsm4(st + ob[n], f[n]); ldsm4(st + oa[n], r0[n]); ldsm4(st + oa[n] + 12288, r1[n]); }
            sched_fence(sink);
#pragma unroll
            for (int k = -1; k < 12; ++k) {
                const int n = (k + 1) / 2 + 2;
                if (n < 6) {
                    if ((k + 1) & 1) ldsm4(st + oa[n] + 12288, r1[n]);
                    else { ldsm4(st + ob[n], f[n]); ldsm4(st + oa[n], r0[n]); }
                }
                if (k == ORDER_AT) bar_arrive(8, 256);
                if (k >= 0) {
                    const int i = k >> 1, h = k & 1;
                    mma16816(T2[h][0], d0[h][0], one[h][0], d0[h][1], one[h][1], r0[i][2 * h], r0[i][2 * h + 1]);
                    mma16816(T2[h][1], d1[h][0], one[2 + h][0], d1[h][1], one[2 + h][1], r1[i][2 * h], r1[i][2 * h + 1]);
                    mma16816(S2[h][0], qk[k][0], qk[k][1], qk[k][2], qk[k][3], r0[i][2 * h], r0[i][2 * h + 1]);
                    mma16816(S2[h][1], qk[k][0], qk[k][1], qk[k][2], qk[k][3], r1[i][2 * h], r1[i][2 * h + 1]);
                }
                if (k < 11) {
                    const int i = (k + 1) >> 1, h = (k + 1) & 1;
#pragma unroll
                    for (int c = 0; c < 2; ++c) {
                        r0[i][2 * h + c] = badd2v(r0[i][2 * h + c], f[i][2 * h + (c ^ 1)]); r1[i][2 * h + c] = badd2v(r1[i][2 * h + c], f[i][2 * h + (c ^ 1)]);
                        d0[h][c] = negv(r0[i][2 * h + c]); d1[h][c] = negv(r1[i][2 * h + c]);
                    }
                    sched_fence(sink);
                }
            }
            float S[2][4], T[2][4];
#pragma unroll
            for (int b = 0; b < 2; ++b)
#pragma unroll
                for (int c = 0; c < 4; ++c) { S[b][c] = S2[0][b][c] + S2[1][b][c]; T[b][c] = T2[0][b][c] + T2[1][b][c]; }
            uint32_t rb[2];
#pragma unroll
            for (int b = 0; b < 2; ++b) {
                const float qd = odd ? T[b][1] : T[b][0], sd = odd ? T[b][3] : T[b][2];
                const float rd = rsq(fmaxf(fmaf(qd, -(float)CH, fmaf(-sd, sd, EPS2)), EPS2));
                const float hi = __uint_as_float(__float_as_uint(rd) & dmask);
                rb[b] = pack2(fmaf(rd, dsel, -hi), hi);
            }
            float rs[4] = {0.f, 0.f, 0.f, 0.f};
            mma16816(rs, 0x3F803F80u, 0u, 0u, 0x3F803F80u, rb[0], rb[1]);
            float y[2][4], z[2][4], p[2][4];
            uint32_t pp[4];
#pragma unroll
            for (int b = 0; b < 2; ++b) {
                y[b][0] = fmaf(-T[b][2], R0, S[b][0]); y[b][1] = fmaf(-T[b][3], R0, S[b][1]);
                y[b][2] = fmaf(-T[b][2], R1, S[b][2]); y[b][3] = fmaf(-T[b][3], R1, S[b][3]);
            }
            auto softmax_p = [&](uint32_t pb) {
#pragma unroll
                for (int b = 0; b < 2; ++b) {
                    z[b][0] = fmaf(rs[2 * b], y[b][0], -m0); z[b][1] = fmaf(rs[2 * b + 1], y[b][1], -m0);
                    z[b][2] = fmaf(rs[2 * b], y[b][2], -m1); z[b][3] = fmaf(rs[2 * b + 1], y[b][3], -m1);
#pragma unroll
                    for (int c = 0; c < 4; ++c) p[b][c] = ex2(z[b][c]);
                    pp[2 * b] = pack2(p[b][0] * rs[2 * b], p[b][1] * rs[2 * b + 1]);
                    pp[2 * b + 1] = pack2(p[b][2] * rs[2 * b], p[b][3] * rs[2 * b + 1]);
                }
                stsm4(pst + pb, pp[0], pp[1], pp[2], pp[3]);
            };
            softmax_p(pbuf);
            const float zmax = fmaxf(fmaxf(fmaxf(z[0][0], z[0][1]), fmaxf(z[0][2], z[0][3])), fmaxf(fmaxf(z[1][0], z[1][1]), fmaxf(z[1][2], z[1][3])));
            ++seq;
            sink_if(SM_FLAG + (pbuf >> 9), seq, zmax > RESCALE_TH);
            const uint32_t info = lds32(SM_INFO + 4 * s);
            bar_sync(1, 256);
            const float k0 = l0, k1 = l1;
            l0 += (p[0][0] + p[0][1]) + (p[1][0] + p[1][1]);
            l1 += (p[0][2] + p[0][3]) + (p[1][2] + p[1][3]);
            const uint32_t flag = lds32(SM_FLAG + (pbuf >> 9));
            mbar_arrive_if(BAR_EMPTY + 8 * s, first);
            pbuf ^= 2048;
            st += STAGE_BYTES;
            if (++s == STAGES) { s = 0; st = 0; ph ^= 1; }
            auto hand_over = [&](uint32_t fl) {
                const float e = (odj ? l1 : l0) + __shfl_xor_sync(0xffffffffu, odj ? l0 : l1, 1);
                const uint32_t ow = ldsv32(SM_OW + (loff >> 12) * 4);
                const float2 pub = ldsf2(SM_OW + 32 + (loff >> 12) * 8);
                const float e2 = __shfl_xor_sync(0xffffffffu, e, 2);
                float cnt = m0 == pub.x && m1 == pub.y && ow != ~0u ? 1.f : 2049.f, wt = odj ? bf_hi(ow) : bf_lo(ow);
                const char* ap = reinterpret_cast<const char*>(sc->A) + (loff >> 12 << 10) + ((loff & 16) >> 1);
                uint32_t on = seq != 1 && !(pst & 32);
                asm volatile("" : "+f"(cnt), "+f"(wt), "+l"(ap), "+r"(on));
                const float tot = e + e2;
                asm volatile("{\n.reg .pred p, q;\n.reg .f32 v;\nmul.f32 v, %1, %2;\nsetp.ne.u32 q, %5, %6;\nsetp.ne.and.u32 p, %4, 0, q;\n"
                             "@p red.relaxed.gpu.global.add.v2.f32 [%0], {v, %3};\n}"
                             ::"l"(ap), "f"(tot), "f"(wt), "f"(cnt), "r"(on), "r"(fl), "r"(seq) : "memory");
                sched_fence(sink);
                stsf(lst, tot * (1.f / CH));
            };
            if (info & 1) {
                hand_over(flag);
                if (info == 1 && flag != seq) goto publish;
            }
            if (flag != seq && !(info & 3)) continue;
            if (flag == seq) {
                const int tz = tid + lds32(SM_EP + 4), w = tz >> 5, g = tz >> 2 & 7, j = tz & 3;
                float x0 = fmaxf(fmaxf(rs[0] * y[0][0], rs[1] * y[0][1]), fmaxf(rs[2] * y[1][0], rs[3] * y[1][1]));
                float x1 = fmaxf(fmaxf(rs[0] * y[0][2], rs[1] * y[0][3]), fmaxf(rs[2] * y[1][2], rs[3] * y[1][3]));
                x0 = fmaxf(x0, __shfl_xor_sync(0xffffffffu, x0, 1)); x0 = fmaxf(x0, __shfl_xor_sync(0xffffffffu, x0, 2));
                x1 = fmaxf(x1, __shfl_xor_sync(0xffffffffu, x1, 1)); x1 = fmaxf(x1, __shfl_xor_sync(0xffffffffu, x1, 2));
                stsf(SM_MX + (w * 16 + g + (j & 1) * 8) * 4, (j & 1) ? x1 : x0);
                bar_sync(2, 128);
                float n0 = m0, n1 = m1;
#pragma unroll
                for (int u = 0; u < 4; ++u) { n0 = fmaxf(n0, ldsf(SM_MX + (u * 16 + g) * 4)); n1 = fmaxf(n1, ldsf(SM_MX + (u * 16 + g + 8) * 4)); }
                n0 = ceilf(n0); n1 = ceilf(n1);
                n0 = __uint_as_float((__float_as_uint(n0) + (n0 > 0.f ? __float_as_uint(n0) & 1u : 0u)) & ~1u);
                const float a0 = ex2(m0 - n0), a1 = ex2(m1 - n1);
                m0 = n0; m1 = n1;
                stsf(SM_AL + j * 32 + g * 4, j == 0 ? a0 : j == 1 ? a1 : j == 2 ? n0 : n1);
                bar_arrive(3, 256);
                softmax_p(pbuf ^ 2048);
                bar_sync(1, 256);
                l0 = fmaf(k0, a0, (p[0][0] + p[0][1]) + (p[1][0] + p[1][1]));
                l1 = fmaf(k1, a1, (p[0][2] + p[0][3]) + (p[1][2] + p[1][3]));
                if (info & 1) hand_over(0);
            }
            if (info & 2) {
                s += 3; st += 3 * STAGE_BYTES;
                if (s >= STAGES) { s -= STAGES; st -= STAGES * STAGE_BYTES; ph ^= 1; }
            }
            if (!(info & 1)) continue;
        publish:
            asm volatile("{\n.reg .pred p;\nsetp.ne.u32 p, %0, 0;\n@p bar.arrive 2, 128;\n@p exit;\n}" ::"r"((uint32_t)(seq != 1 && w != 0)) : "memory");
            const uint32_t epoch = lds32(SM_EP);
            uint32_t lsa = lst & ~140u;
            asm volatile("" : "+r"(lsa));
            bar_sync(2, 128);
            {
                uint32_t la[4], lb[4];
                lds128(lsa, la); lds128(lsa + 128, lb);
                const float sa = sum4(la), sb = sum4(lb);
                const uint32_t mt = __float_as_uint(m0) | ((epoch ^ (seq == 1)) & 1u);
                const float ha = __uint_as_float(__float_as_uint(sa) & 0xffff0000u), hb = __uint_as_float(__float_as_uint(sb) & 0xffff0000u);
                st_v4(reinterpret_cast<uint4*>(reinterpret_cast<char*>(sc->L) + loff), pack2(ha, sa - ha), pack2(hb, sb - hb), mt, __float_as_uint(m1));
            }
            if (seq != 1) return;
            sink_if(SM_EP + 8, sink, lds32(SM_EP + 4));
            m0 = m1 = -INFINITY; l0 = l1 = 0.f;
            const int tz = tid + lds32(SM_EP + 4), w = tz >> 5, lane = tz & 31;
            uint4 v[3];
            unsigned it = 0;
            while (true) {
                if (it < 2 && src >= NSERV) mbar_wait(BAR_FULL + 8 * (QK_AFTER + it), 0);
#pragma unroll
                for (int k = 0; k < 3; ++k) v[k] = ld_relaxed4(&sc->qk[(3 * w + k) * 32 + lane]);
                const uint32_t bad = (v[0].x ^ epoch) | (v[1].x ^ epoch) | (v[2].x ^ epoch);
                if (__all_sync(0xffffffffu, (bad & 1u) == 0)) break;
                spin_guard(++it);
            }
            bar_sync(6, 256);
#pragma unroll
            for (int k = 0; k < 3; ++k) stsm4(SM_XA + (3 * w + k) * 512 + lane * 16, v[k].x, v[k].y, v[k].z, v[k].w);
            bar_sync(2, 128);
#pragma unroll
            for (int k = 0; k < 12; ++k) ldsm4(SM_XA + k * 512 + lane * 16, qk[k]);
            asm volatile("fence.proxy.async.shared::cta;" ::: "memory");
            bar_sync(2, 128);
            mbar_arrive_if(BAR_EMPTY + 8 * (STAGES - 1), tz == 0);
            first = tz == 0;
            float r[4] = {0.f, 0.f, 0.f, 0.f}, r2[4] = {0.f, 0.f, 0.f, 0.f};
#pragma unroll
            for (int k = 0; k < 12; k += 2) {
                mma16816(r, qk[k][0], qk[k][1], qk[k][2], qk[k][3], 0x3F803F80u, 0x3F803F80u);
                mma16816(r2, qk[k + 1][0], qk[k + 1][1], qk[k + 1][2], qk[k + 1][3], 0x3F803F80u, 0x3F803F80u);
            }
            R0 = (r[0] + r2[0]) * (1.f / CH); R1 = (r[2] + r2[2]) * (1.f / CH);
        }
    } else if (warp < 8) {
        asm volatile("setmaxnreg.inc.sync.aligned.u32 256;");
        const uint32_t cb = opaque(cb0, lane);
        pad<4>();
        const int h = __shfl_sync(0xffffffffu, warp - 4, 0);
        uint32_t oa[3], ob[3];
#pragma unroll
        for (int b = 0; b < 3; ++b) {
            int cc = 6 * h + 2 * b + (m4 >> 1);
            int r = 3 * r8 + (cc >> 3);
            oa[b] = opaque(SB + (m4 & 1) * 12288 + r * 128 + (((cc & 7) ^ (r & 7)) << 4), lane);
            cc = 6 * h + 2 * b + (m4 & 1);
            r = 3 * (4 * (m4 >> 1) + (r8 >> 1)) + (cc >> 3);
            ob[b] = opaque(SB + 24576 + r * 128 + (((cc & 7) ^ (r & 7)) << 4), lane);
        }
        const uint32_t l16 = opaque(lane * 16, lane);
        const uint32_t vdst = opaque(mapa(SM_A + (bid & (CL - 1)) * 832 + h * 192 + ((j ^ (bid >> 1 & 3)) << 4), g), lane), vbar = opaque(mapa(BAR_V, g), lane);
        uint32_t axb = SM_XA;
        float acc[6][4];
#pragma unroll
        for (int t = 0; t < 6; ++t) acc[t][0] = acc[t][1] = acc[t][2] = acc[t][3] = 0.f;
        int s = STAGES - 1; uint32_t ph = 1, pbuf = 0;
        uint32_t wf[12][3][4];
#pragma unroll
        for (int i = 0; i < 12; ++i)
#pragma unroll
            for (int c = 0; c < 4; ++c) wf[i][0][c] = wf[i][1][c] = wf[i][2][c] = 0u;
        uint32_t seq = 0, info = 0, sink = 0;
        mbar_wait(BAR_EP, 0);
        uint32_t par = ~lds32(SM_EP) & 1u;
        st_v4_if(&sc->M[(g * 128 + src) * 2 + (j & 1)], 0u, 0u, par, 0u, ((j & 2) | h) == 0);
#pragma unroll 1
        while (true) {
            if (info & 8) {
                const uint32_t lz = l16 + lds32(SM_EP + 4);
                const uint32_t pub0 = lds32(SM_AL + 64 + (lz >> 6 << 2)), pub1 = lds32(SM_AL + 96 + (lz >> 6 << 2));
                if (h == 0) stsf2(SM_OW + 32 + (lz >> 6 << 3), __uint_as_float(pub0), __uint_as_float(pub1));
                st_v4_if(&sc->M[((lz >> 6) * 128 + src) * 2 + (lz >> 4 & 1)], 0u, 0u, pub0 | par, pub1, ((lz & 32) | h) == 0);
            }
            if (info & 2) {
                const uint32_t lz = l16 + lds32(SM_EP + 4);
                asm volatile("barrier.cluster.wait.aligned;" ::: "memory");
#pragma unroll
                for (int c = 0; c < 3; ++c) {
                    mbar_wait(BAR_FULL + 8 * s, ph);
#pragma unroll
                    for (int i = 0; i < 12; ++i) ldsm4(SB + s * STAGE_BYTES + (h * 12 + i) * 512 + lz, wf[4 * c + i / 3][i % 3]);
                    bar_sync(4, 128);
                    mbar_arrive_if(BAR_EMPTY + 8 * s, (lz | h) == 0);
                    if (++s == STAGES) { s = 0; ph ^= 1; }
                }
            }
            if (info & 4) {
                float u0 = 0.f, u1 = 0.f;
#pragma unroll
                for (int t = 0; t < 6; ++t) { u0 += acc[t][0] + acc[t][1]; u1 += acc[t][2] + acc[t][3]; }
                const uint32_t lz = l16 + lds32(SM_EP + 4);
                const bool j1 = lz & 16;
                const float e = (j1 ? u1 : u0) + __shfl_xor_sync(0xffffffffu, j1 ? u0 : u1, 1);
                stsf(SM_UL + (lz & 16) * 8 + (lz >> 6 << 4) + h * 4, (e + __shfl_xor_sync(0xffffffffu, e, 2)) * (1.f / CH));
                bar_sync(4, 128);
                uint32_t ua[4], ub[4];
                lds128(SM_UL + (lz >> 6 << 4), ua); lds128(SM_UL + 128 + (lz >> 6 << 4), ub);
                u0 = sum4(ua); u1 = sum4(ub);
#pragma unroll
                for (int t = 0; t < 6; ++t) { acc[t][0] -= u0; acc[t][1] -= u0; acc[t][2] -= u1; acc[t][3] -= u1; }
            }
            auto project = [&]() {
                uint32_t af[12][4], ax[4];
#pragma unroll
                for (int i = 0; i < 4; ++i) ax[i] = axb + ((h + i) & 3) * 1536;
                const uint32_t real = seq != 1;
#pragma unroll
                for (int ks = 0; ks < 3; ++ks) {
                    af[ks][0] = pack2(acc[2 * ks][0], acc[2 * ks][1]); af[ks][1] = pack2(acc[2 * ks][2], acc[2 * ks][3]);
                    af[ks][2] = pack2(acc[2 * ks + 1][0], acc[2 * ks + 1][1]); af[ks][3] = pack2(acc[2 * ks + 1][2], acc[2 * ks + 1][3]);
                    stsm4(ax[0] + ks * 512 + l16, af[ks][0], af[ks][1], af[ks][2], af[ks][3]);
                }
                float o[4][2][4];
                constexpr int ord[36] = {0,1,2,0,1,2,0,1,2, 0,1,0,2,0,1,0,1,0,2,0,1,0,1,0,1,0, 1,2,1,2,1, 2,3,2,3,2};
                int nx[3] = {0, 0, 0};
                bool used3 = false;
#pragma unroll
                for (int z = 0; z < 36; ++z) {
                    const int a = ord[z], tp = a == 3 ? 2 : a, i = nx[tp]++;
                    if (i == 0 || (a == 3 && !used3)) {
#pragma unroll
                        for (int c = 0; c < 4; ++c) o[a][0][c] = o[a][1][c] = 0.f;
                    }
                    if (a == 3) used3 = true;
                    mma16816(o[a][0], af[i][0], af[i][1], af[i][2], af[i][3], wf[i][tp][0], wf[i][tp][1]);
                    mma16816(o[a][1], af[i][0], af[i][1], af[i][2], af[i][3], wf[i][tp][2], wf[i][tp][3]);
                    if (z == 0 || z == 2 || z == 30) sched_fence(sink);
                    if (z == 2) bar_sync(4, 128);
                    if (z == REL_Z) asm volatile("{\n.reg .pred p;\nsetp.ne.u32 p, %0, 0;\n@p bar.arrive 12, 256;\n}" ::"r"(real) : "memory");
#pragma unroll
                    for (int k = 0; k < 9; ++k) if (z == 2) ldsm4(ax[1 + k / 3] + (k % 3) * 512 + l16, af[3 + k]);
#pragma unroll
                    for (int e = 0; e < 3; ++e)
                        if (z == (e == 0 ? 26 : e == 1 ? 31 : 35)) {
                            if (e == 2) {
#pragma unroll
                                for (int c = 0; c < 4; ++c) { o[2][0][c] += o[3][0][c]; o[2][1][c] += o[3][1][c]; }
                            }
                            st_async_if(vdst + e * 64, pack2(o[e][0][0], o[e][0][1]), pack2(o[e][1][0], o[e][1][1]),
                                        pack2(o[e][0][2], o[e][0][3]), pack2(o[e][1][2], o[e][1][3]), vbar, real);
                        }
                }
            };
            if (!(info & 1)) {
                const uint32_t st = __shfl_sync(0xffffffffu, s * STAGE_BYTES, 0);
                axb = SB + st;
                const uint32_t lz = l16 + lds32(SM_EP + 4);
                const char* tp = reinterpret_cast<const char*>(sc->T) + ((lz >> 5 << 12) + (lz & 16) + src * 32);
                uint32_t ann = (lz >> 8 | h) == 0;
                asm volatile("" : "+l"(tp), "+r"(ann));
                mbar_wait(BAR_FULL + 8 * s, ph);
                asm volatile("{\n.reg .pred p;\n.reg .b32 t, u;\nld.shared.u32 %0, [%1];\nmov.u32 t, %%globaltimer_lo;\nlop3.b32 t, t, 1, %3, 0xba;\n"
                             "and.b32 u, %0, %4;\nsetp.ne.u32 p, u, 0;\n@p st.relaxed.gpu.global.v4.u32 [%2], {t,t,t,t};\n}"
                             : "=r"(info) : "r"(SM_INFO + 4 * s), "l"(tp), "r"(par), "r"(ann) : "memory");
                bar_sync(8, 256);
                uint32_t xt[4][3][4];
#pragma unroll
                for (int u = 0; u < 6; ++u) {
                    const int gp = u / 3, b = u % 3;
                    if (u == 5) asm volatile("{\n.reg .pred p;\nsetp.ne.u32 p, %0, 0;\n@p bar.arrive 11, 256;\n}" ::"r"((uint32_t)((info & 1) && seq != 0)) : "memory");
                    uint32_t f[4];
                    ldsm4t(st + ob[b] + gp * 3072, f);
                    ldsm4t(st + oa[b] + (2 * gp) * 3072, xt[2 * gp][b]);
                    ldsm4t(st + oa[b] + (2 * gp + 1) * 3072, xt[2 * gp + 1][b]);
                    if (u == 1 || u == 3) sched_fence(sink);
#pragma unroll
                    for (int c = 0; c < 4; ++c) {
                        xt[2 * gp][b][c] = badd2v(xt[2 * gp][b][c], f[c >> 1]);
                        xt[2 * gp + 1][b][c] = badd2v(xt[2 * gp + 1][b][c], f[2 + (c >> 1)]);
                    }
                }
                ++seq;
                const uint32_t pb = pbuf;
                pbuf ^= 2048;
                if (++s == STAGES) { s = 0; ph ^= 1; }
                auto accumulate = [&]() {
                    uint32_t pa[4][4], fa = SM_FLAG + (pb >> 9);
#pragma unroll 1
                    while (true) {
                        if (fa == SM_EP + 4) {
                            bar_sync(3, 256);
                            const uint32_t gz = (l16 + lds32(SM_EP + 4)) >> 6 << 2;
                            const float a0 = ldsf(SM_AL + gz), a1 = ldsf(SM_AL + 32 + gz);
#pragma unroll
                            for (int t = 0; t < 6; ++t) { acc[t][0] *= a0; acc[t][1] *= a0; acc[t][2] *= a1; acc[t][3] *= a1; }
                        }
                        bar_sync(1, 256);
                        uint32_t flag;
                        asm volatile("ld.shared.u32 %4, [%6];\nldmatrix.sync.aligned.m8n8.x4.shared.b16 {%0,%1,%2,%3}, [%5];"
                                     : "=r"(pa[0][0]), "=r"(pa[0][1]), "=r"(pa[0][2]), "=r"(pa[0][3]), "=r"(flag) : "r"(SM_P + l16 + pb), "r"(fa) : "memory");
                        fa = SM_EP + 4;
                        if (flag != seq) break;
                    }
#pragma unroll
                    for (int gq = 1; gq < 4; ++gq) ldsm4(SM_P + l16 + pb + gq * 512, pa[gq]);
#pragma unroll
                    for (int gq = 0; gq < 4; ++gq)
#pragma unroll
                        for (int b = 0; b < 3; ++b) {
                            mma16816(acc[2 * b], pa[gq][0], pa[gq][1], pa[gq][2], pa[gq][3], xt[gq][b][0], xt[gq][b][1]);
                            mma16816(acc[2 * b + 1], pa[gq][0], pa[gq][1], pa[gq][2], pa[gq][3], xt[gq][b][2], xt[gq][b][3]);
                        }
                };
                if (info != 1) { accumulate(); continue; }
                accumulate();
                project();
            } else {
                project();
            }
            if (seq != 1) break;
            sink_if(SM_EP + 8, sink, lds32(SM_EP + 4));
            asm volatile("fence.proxy.async.shared::cta;" ::: "memory");
            bar_arrive(6, 256);
            par ^= 1u;
            info = 0;
#pragma unroll
            for (int t = 0; t < 6; ++t) acc[t][0] = acc[t][1] = acc[t][2] = acc[t][3] = 0.f;
        }
    } else {
        asm volatile("setmaxnreg.dec.sync.aligned.u32 72;");
        const uint32_t cb = opaque(cb0, lane);
        const int fw = __shfl_sync(0xffffffffu, warp - 8, 0);
        if (fw == 0) {
            if (src < NSERV) {
                el_expect_tx(BAR_FULL, STAGE_BYTES);
                el_tile(cb, 0, JOIN_N * NE + src, &tm0, &tm1);
            }
            el_expect_tx(BAR_FULL + 8, STAGE_BYTES);
            el_tile(cb, 1, src < NSERV ? JOIN_N * NE + NS + src : src - NSERV + NE, &tm0, &tm1);
            el_arrive(BAR_FULL);
        } else if (fw == 1) {
            const unsigned epoch = __shfl_sync(0xffffffffu, ticket + 1, 0);
            sts32(SM_EP, epoch);
            el_arrive(BAR_EP);
            stsf2(SM_FLAG + 8, __uint_as_float(now_ns()), __uint_as_float(clk32()));
            __nanosleep(6000);
            unsigned it = 0;
            while (!__all_sync(0xffffffffu, ld_acquire(sc->flagW + min(lane, NSERV - 1) * 8) == epoch)) { spin_guard(++it); __nanosleep(64); }
            asm volatile("fence.proxy.async;" ::: "memory");
            __syncwarp();
            el_arrive(BAR_W);
        } else if (fw == 3) {
            if (lane < CL) sts32(SM_OW + 4 * lane, ~0u);
            asm volatile("barrier.cluster.arrive.relaxed.aligned;" ::: "memory");
        }
        uint32_t sink = 0;
        int slot = 2, n = fw ? 0 : src < NSERV ? JOIN_N + 2 : 2, sp = 1, sd = 0;
        uint32_t pp = 0, pd = 0;
#pragma unroll 1
        for (int real = 0; ; ++real) {
        {
            const int wat = CHECKPOINT + (bid & WSTAG), pause = real ? 0 : PAUSE + (bid >> 4 & 7);
            auto wait_empty = [&](int sl) {
                const int r = (sl * 37) >> 8, st = sl - r * STAGES;
                mbar_wait_u(BAR_EMPTY + 8 * st, (r ^ (st != STAGES - 1)) & 1);
                return st;
            };
            while (n != pause && n != 0) {
                const int t = n < JOIN_N ? src - NSERV + n * NE : n < NSTATIC ? src + n * NS - JOIN_N * NSERV : NSTATIC * NS - JOIN_N * NSERV + __shfl_sync(0xffffffffu, ticket, 0);
                const bool done = t >= NTILES, winj = n == wat || (done && n < wat);
                sts32(SM_INFO + 4 * sp, done + 2 * winj + 4 * ((unsigned)(NTILES - END_X - t) < (unsigned)(2 * NS)) + 8 * (n == MX_AT || (done && n < MX_AT)));
                sts32(SM_INFO + 4 * STAGES, done ? ~0u : n);
                el_arrive(BAR_FULL + 8 * sp);
                const int wslot = slot;
                if (winj) slot += 3;
                if (!done) {
                    const int s = wait_empty(slot);
                    el_expect_tx(BAR_FULL + 8 * s, STAGE_BYTES);
                    mbar_wait_u(BAR_FULL + 8 * sd, pd);
                    if (n >= MID_FROM || t >= NTILES - END_X) {
                        const uint32_t c0 = clk32(), hold = t >= NTILES - END_X ? D_END : MID_D;
                        while (clk32() - c0 < hold && !mbar_test(BAR_FULL + 8 * sp, pp)) __nanosleep(50);
                    }
                    asm volatile("{\n.reg .pred p;\nsetp.ne.u32 p, %2, 0;\n@p atom.relaxed.gpu.global.inc.u32 %0, [%1], 0x7fffffff;\n}"
                                 : "+r"(ticket) : "l"(&sc->ctr), "r"((uint32_t)(n >= NSTATIC - 1 && lane == 0)) : "memory");
                    el_tile(cb, s, t, &tm0, &tm1);
                    sd = sp; pd = pp; sp = s; pp = ((slot * 37) >> 8) & 1;
                    ++n;
                    if (++slot >= 2 * STAGES) slot -= 2 * STAGES;
                } else {
                    n = 0;
                }
                if (winj) {
                    mbar_wait_u(BAR_W, 0);
#pragma unroll 1
                    for (int c = 0; c < 3; ++c) {
                        const int st = wait_empty(wslot + c);
                        el_expect_tx(BAR_FULL + 8 * st, 24576);
                        el_bulk(SB + st * STAGE_BYTES, sc->wvo + c * 6144, 24576, BAR_FULL + 8 * st);
                        el_arrive(BAR_FULL + 8 * st);
                    }
                }
            }
        }
        if (fw == 0) bar_arrive(7, 128);
        {
            const int ft = tid - 256 + lds32(SM_EP + 4), lane = ft & 31, g = lane >> 2, j = lane & 3;
            const int n0 = src & (CL - 1);
            const uint32_t epoch = lds32(SM_EP), par = epoch & 1u;
            unsigned it = 0;
            if (fw == 1 && real) {
                const uint4* xp = &(real > 1 ? sc->L : sc->M)[(n0 * 128 + lane) * 2];
                uint4 x[4];
                while ((uint32_t)ldsv32(SM_INFO + 4 * STAGES) < WT_AT) { __nanosleep(1000); spin_guard(++it); }
                while (true) {
#pragma unroll
                    for (int i = 0; i < 4; ++i) {
                        x[i] = make_uint4(0u, 0u, 0xff7ffffeu | par, 0xff7fffffu);
                        ld_relaxed4_if(x[i], xp + 64 * i, 32 * i + lane < NS);
                    }
                    if (!__any_sync(0xffffffffu, ((x[0].z ^ par) | (x[1].z ^ par) | (x[2].z ^ par) | (x[3].z ^ par)) & 1u)) break;
                    if (real == 1) __nanosleep(1000);
                    spin_guard(++it);
                }
#pragma unroll
                for (int i = 0; i < 4; ++i) x[i].z &= ~1u;
                const float Xa = warp_max(fmaxf(fmaxf(__uint_as_float(x[0].z), __uint_as_float(x[1].z)), fmaxf(__uint_as_float(x[2].z), __uint_as_float(x[3].z))));
                const float Xb = warp_max(fmaxf(fmaxf(__uint_as_float(x[0].w), __uint_as_float(x[1].w)), fmaxf(__uint_as_float(x[2].w), __uint_as_float(x[3].w))));
                uint32_t own = 0;
#pragma unroll
                for (int i = 0; i < 4; ++i) {
                    const uint32_t w2 = pack2(ex2(__uint_as_float(x[i].z) - Xa), ex2(__uint_as_float(x[i].w) - Xb));
                    if (i == src >> 5) own = w2;
                    sts16(SM_FW + (32 * i + lane) * 2, w2); sts16(SM_FW + 272 + (32 * i + lane) * 2, w2 >> 16);
                }
                __syncwarp();
                el_arrive(BAR_WT);
                if (real == 1) {
                    asm volatile("barrier.cluster.wait.aligned;" ::: "memory");
                    asm volatile("{\n.reg .pred p;\nsetp.ne.u32 p, %2, 0;\n@p st.relaxed.cluster.shared::cluster.u32 [%0], %1;\n}"
                                 ::"r"(mapa(SM_OW + n0 * 4, lane & (CL - 1))), "r"(own), "r"((uint32_t)(((lane ^ src) >> 3 & 3) == 0)) : "memory");
                }
            }
            const uint32_t valid = real && 32 * fw + lane < NS;
            const uint4* lp = scl + (n0 * 128 + min(32 * fw + lane, NS - 1)) * 2;
            sched_fence(sink);
            if (fw) bar_sync(7, 128);
            else mbar_wait_u(real ? BAR_WT : BAR_EP, real ? ~real & 1 : 0);
            uint32_t av = lds32(SM_FW + (g & 1) * 272 + (src & ~(CL - 1)) * 2 + j * 4);
            asm volatile("mul.rn.bf16x2 %0, %0, %1;" : "+r"(av) : "r"(0x43404340u));
            const float2 ts = ldsf2(SM_FLAG + 8);
            uint32_t t0 = __float_as_uint(ts.x);
            const float nspc = fminf(__fdividef((float)(now_ns() - t0), (float)(clk32() - __float_as_uint(ts.y))), 2.f);
            uint32_t llag = t0 + MEMNS + f2uv(nspc * LLAG);
            uint32_t vsrc = SM_A + (lane & 7) * 832 + fw * 192 + (((lane >> 3) ^ (lane >> 1 & 3)) << 4), vb = real ? BAR_V : BAR_EP;
            uint32_t id = 0x3210 + lds32(SM_EP + 4), chk = valid ? ~0u : 0u, on = real == 1;
            uint32_t wr = real && (g & 1) == (j >> 1) ? g >> 1 : 3, epw = real;
            __nv_bfloat16* op = out + (n0 + (j >> 1) * 8) * CH + 48 * fw + 8 * (j & 1) + 16 * (g >> 1);
            const float2* ap = reinterpret_cast<const float2*>(&sc->A[n0 * 64]) + (j >> 1);
            float want = real ? (float)(4 * NS) : 0.f;
            asm volatile("" : "+l"(lp), "+l"(op), "+l"(ap), "+r"(vsrc), "+r"(vb), "+r"(chk), "+r"(wr), "+r"(id), "+r"(av), "+r"(on), "+r"(epw), "+f"(want), "+r"(llag), "+r"(t0));
            sched_fence(sink);
            if (real == 1) bar_sync(11, 256);
            {
                sts32(SM_FIN + fw * 4, __reduce_max_sync(0xffffffffu, (collect(lp + 8 * 128 * 2, par, on) - t0) & (on ? chk : 0u)));
                bar_sync(13, 128);
                uint32_t t4[4];
                lds128(SM_FIN, t4);
                llag += max(max(t4[0], t4[1]), max(t4[2], t4[3]));
                asm volatile("{\n.reg .pred p;\nsetp.eq.u32 p, %2, 0;\n@p st.global.v2.u32 [%0], {%1, %2};\n}" ::"l"(&sc->epoch), "r"(epoch), "r"(src | fw | lane | !on) : "memory");
            }
            if (real == 1) bar_sync(12, 256);
            float2 la = make_float2(1.f, 0.f);
            load_at(la, on, llag, ap, id);
            mbar_wait_u(vb, 0);
            float r[8];
            {
                uint32_t bv[3][4];
#pragma unroll
                for (int u = 0; u < 3; ++u) ldsm4t(vsrc + u * 64, bv[u]);
                float cv[6][4];
#pragma unroll
                for (int u = 0; u < 6; ++u) {
                    cv[u][0] = cv[u][1] = cv[u][2] = cv[u][3] = 0.f;
                    mma16816(cv[u], av, 0u, 0u, av, bv[u >> 1][2 * (u & 1)], bv[u >> 1][2 * (u & 1) + 1]);
                }
#pragma unroll
                for (int i = 0; i < 8; ++i) r[i] = wr == 0 ? cv[i >> 2][i & 3] : wr == 1 ? cv[2 + (i >> 2)][i & 3] : cv[4 + (i >> 2)][i & 3];
            }
            asm volatile("" : "+f"(r[0]), "+f"(r[1]), "+f"(r[2]), "+f"(r[3]), "+f"(r[4]), "+f"(r[5]), "+f"(r[6]), "+f"(r[7]));
            sched_fence(sink);
            asm volatile("{\n.reg .pred p, q;\n.reg .f32 i, t<8>;\n.reg .b32 a, b, c, d;\n"
                         "rcp.approx.ftz.f32 i, %0;\nsetp.eq.f32 q, %1, %2;\nsetp.lt.and.u32 p, %11, 3, q;\n"
                         "mul.f32 t0, %3, i;\nmul.f32 t1, %4, i;\nmul.f32 t2, %5, i;\nmul.f32 t3, %6, i;\n"
                         "mul.f32 t4, %7, i;\nmul.f32 t5, %8, i;\nmul.f32 t6, %9, i;\nmul.f32 t7, %10, i;\n"
                         "cvt.rn.bf16x2.f32 a, t1, t0;\ncvt.rn.bf16x2.f32 b, t3, t2;\ncvt.rn.bf16x2.f32 c, t5, t4;\ncvt.rn.bf16x2.f32 d, t7, t6;\n"
                         "@p red.global.add.noftz.v4.bf16x2 [%12], {a, b, c, d};\n"
                         "setp.ne.and.u32 p, %13, 0, q;\n@p exit;\n"
                         "}"
                         ::"f"(la.x), "f"(la.y), "f"(want), "f"(r[0]), "f"(r[1]), "f"(r[2]), "f"(r[3]), "f"(r[4]), "f"(r[5]), "f"(r[6]), "f"(r[7]),
                           "r"(wr), "l"(op), "r"(epw) : "memory");
            uint32_t redo = 0;
            if (la.y != want) {
                float L;
                if (real == 1) {
                    while ((f2uv(la.y) & 2047u) != (unsigned)(4 * NS)) {
                        asm volatile("ld.relaxed.gpu.global.v2.f32 {%0,%1}, [%2];" : "=f"(la.x), "=f"(la.y) : "l"(ap) : "memory");
                        spin_guard(++it);
                    }
                    redo = la.y != want;
                    L = la.x;
                } else {
                    const int lz = lane + lds32(SM_EP + 4), gz = lz >> 2, jz = lz & 3;
                    uint32_t wa[4], b[4];
                    const float2 x = ldsf2(SM_FW + (gz & 1) * 272 + fw * 64 + jz * 8), y = ldsf2(SM_FW + (gz & 1) * 272 + fw * 64 + 32 + jz * 8);
                    wa[0] = __float_as_uint(x.x); wa[1] = __float_as_uint(x.y); wa[2] = __float_as_uint(y.x); wa[3] = __float_as_uint(y.y);
                    const uint32_t ldst = SB + (fw * 32 + lz) * 16;
                    uint4 l = make_uint4(0u, 0u, 0u, 0u);
                    ld_relaxed4_if(l, lp, chk);
                    asm volatile("st.shared.v4.u32 [%0], {%1,%2,%3,%4};" ::"r"(ldst), "r"(l.x), "r"(l.y), "r"(l.z), "r"(l.w) : "memory");
                    __syncwarp();
                    ldsm4t(ldst, b);
                    float c[4];
                    mma_sp(c, wa, b);
                    asm volatile("{\n.reg .pred p;\nsetp.ne.u32 p, %2, 0;\n@p st.shared.f32 [%0], %1;\n}"
                                 ::"r"(SM_FIN + 32 + (lz == 5) * 16 + fw * 4), "f"((c[0] + c[2]) + (c[1] + c[3])), "r"((uint32_t)(lz == 0 || lz == 5)) : "memory");
                    bar_sync(13, 128);
                    uint32_t d[4];
                    lds128(SM_FIN + 32 + (jz >> 1) * 16, d);
                    L = sum4(d) * (float)CH;
                }
                float inv;
                asm volatile("rcp.approx.ftz.f32 %0, %1;" : "=f"(inv) : "f"(L));
                red_if(op, pack2(r[0] * inv, r[1] * inv), pack2(r[2] * inv, r[3] * inv), pack2(r[4] * inv, r[5] * inv), pack2(r[6] * inv, r[7] * inv), !redo && wr < 3);
            }
            if (real && !redo) return;
            sink_if(SM_EP + 8, sink, lds32(SM_EP + 4));
            bar_sync(9, 128);
            spin_guard(real);
        }
        }
    }
}

typedef CUresult (*EncodeFn)(CUtensorMap*, CUtensorMapDataType, cuuint32_t, void*, const cuuint64_t*, const cuuint64_t*,
                             const cuuint32_t*, const cuuint32_t*, CUtensorMapInterleave, CUtensorMapSwizzle,
                             CUtensorMapL2promotion, CUtensorMapFloatOOBfill);

}

extern "C" void kernel_launch(void* const* d_in, const int* in_sizes, int n_in, void* d_out, int out_size) {
    (void)in_sizes; (void)n_in; (void)out_size;
    static EncodeFn enc = nullptr;
    static int grid = 0;
    static Scratch* scratch = nullptr;
    if (!enc) {
        cudaDriverEntryPointQueryResult qr;
        cudaGetDriverEntryPoint("cuTensorMapEncodeTiled", (void**)&enc, cudaEnableDefault, &qr);
        cudaGetSymbolAddress((void**)&scratch, g_s);
        int dev = 0, sms = 0;
        cudaGetDevice(&dev);
        cudaDeviceGetAttribute(&sms, cudaDevAttrMultiProcessorCount, dev);
        (void)sms;
        cudaFuncSetAttribute(fused_kernel, cudaFuncAttributeMaxDynamicSharedMemorySize, SM_TOTAL);
        cudaLaunchConfig_t cfg = {};
        cfg.gridDim = dim3(MAXS); cfg.blockDim = dim3(384); cfg.dynamicSmemBytes = SM_TOTAL;
        cudaLaunchAttribute at[1]; at[0].id = cudaLaunchAttributeClusterDimension; at[0].val.clusterDim.x = CL; at[0].val.clusterDim.y = 1; at[0].val.clusterDim.z = 1;
        cfg.attrs = at; cfg.numAttrs = 1;
        int ncl = 0;
        cudaOccupancyMaxActiveClusters(&ncl, fused_kernel, &cfg);
        grid = (ncl < MAXS / CL ? ncl : MAXS / CL) * CL;
    }
    CUtensorMap tm0, tm1, tmq, tmk, tmv, tmo;
    {
        cuuint64_t gd[3] = {64, 1536, 512}; cuuint64_t gs[2] = {128, 196608};
        cuuint32_t bd[3] = {64, 96, 2}; cuuint32_t es[3] = {1, 1, 1};
        enc(&tm0, CU_TENSOR_MAP_DATA_TYPE_BFLOAT16, 3, d_in[1], gd, gs, bd, es, CU_TENSOR_MAP_INTERLEAVE_NONE,
            CU_TENSOR_MAP_SWIZZLE_128B, CU_TENSOR_MAP_L2_PROMOTION_L2_64B, CU_TENSOR_MAP_FLOAT_OOB_FILL_NONE);
    }
    auto map2d = [&](CUtensorMap* tm, void* p, cuuint64_t cols, cuuint64_t rows, cuuint32_t bc, cuuint32_t br, CUtensorMapSwizzle sw) {
        cuuint64_t gd[2] = {cols, rows}; cuuint64_t gs[1] = {cols * 2};
        cuuint32_t bd[2] = {bc, br}; cuuint32_t es[2] = {1, 1};
        enc(tm, CU_TENSOR_MAP_DATA_TYPE_BFLOAT16, 2, p, gd, gs, bd, es, CU_TENSOR_MAP_INTERLEAVE_NONE,
            sw, CU_TENSOR_MAP_L2_PROMOTION_L2_64B, CU_TENSOR_MAP_FLOAT_OOB_FILL_NONE);
    };
    map2d(&tm1, d_in[2], 64, 196608, 64, 48, CU_TENSOR_MAP_SWIZZLE_128B);
    map2d(&tmq, d_in[3], 64, 576, 64, 192, CU_TENSOR_MAP_SWIZZLE_128B);
    map2d(&tmk, d_in[4], 64, 576, 64, 48, CU_TENSOR_MAP_SWIZZLE_128B);
    map2d(&tmv, d_in[5], 64, 576, 64, 192, CU_TENSOR_MAP_SWIZZLE_128B);
    map2d(&tmo, d_in[6], 192, 192, 16, 192, CU_TENSOR_MAP_SWIZZLE_NONE);
    fused_kernel<<<grid, 384, SM_TOTAL>>>((uint64_t)scratch | (grid - 1), (const __nv_bfloat16*)d_in[0], (const char*)d_in[1], (const char*)d_in[2],
                                          (const char*)d_in[3], (const char*)d_in[4], tm0, tm1, tmq, tmk, tmv, tmo, (__nv_bfloat16*)d_out, scratch->L);
}
```

```cpp
#include <cuda_runtime.h>
#include <cuda.h>
#include <cuda_bf16.h>
#include <stdint.h>

namespace {

constexpr int CH = 192;
constexpr int NTILES = 4096;
constexpr int STAGES = 7;
constexpr int STAGE_BYTES = 30720;
constexpr int NSERV = 12;
constexpr int CL = 8;
constexpr int MAXS = 128;
constexpr float LN_EPS = 1e-5f;
constexpr float EPS2 = LN_EPS * CH * CH;
constexpr float RESCALE_TH = 60.0f;
#define NSTATIC 6
#define JOIN_N 3
static_assert(NSTATIC >= JOIN_N + 3, "a service CTA starts with two static tiles and requests its first ticket with the third one");
#define ORDER_AT 7
#define CHECKPOINT 10
#define WSTAG 15
#define MX_AT 9
#define WT_AT (MX_AT + 6)
#define PAUSE 12
#define D_END 1085
#define END_X 240
#define MID_D 675
#define MID_FROM 16
#define QK_AFTER 3
#define MEMNS 164
#define LLAG 950
#define REL_Z 18
template <int N> __device__ __forceinline__ void pad() { if constexpr (N > 0) { asm volatile("pmevent 1;"); pad<N - 1>(); } }
constexpr unsigned SPIN_LIMIT = 1u << 22;
constexpr uint64_t EVICT_FIRST = 0x12F0000000000000ull;

constexpr uint32_t K_SB = 1024;
constexpr uint32_t K_SM_P = K_SB + STAGES * STAGE_BYTES;
constexpr uint32_t K_SM_A = K_SM_P + 4096;
constexpr uint32_t K_SM_XA = K_SB + (STAGES - 1) * STAGE_BYTES;
constexpr uint32_t K_SM_MX = K_SM_A + 6656;
constexpr uint32_t K_SM_UL = K_SM_MX + 256;
constexpr uint32_t K_SM_AL = K_SM_UL + 512;
constexpr uint32_t K_SM_FIN = K_SM_AL + 128;
constexpr uint32_t K_SM_OW = K_SM_FIN + 64;
constexpr uint32_t K_SM_FW = K_SM_OW + 128;
constexpr uint32_t K_SM_ZERO = K_SM_FW + 768;
constexpr uint32_t K_SM_EP = K_SM_ZERO + 256;
constexpr uint32_t K_SM_FLAG = K_SM_EP + 16;
constexpr uint32_t K_BAR_FULL = K_SM_FLAG + 16, K_BAR_EMPTY = K_BAR_FULL + 8 * STAGES, K_BAR_W = K_BAR_EMPTY + 8 * STAGES;
constexpr uint32_t K_BAR_EP = K_BAR_W + 8;
constexpr uint32_t K_BAR_WT = K_BAR_EP + 8;
constexpr uint32_t K_BAR_V = K_BAR_WT + 8;
constexpr uint32_t K_BAR_JOB = K_BAR_V + 24;
constexpr uint32_t K_SM_INFO = K_BAR_JOB + 8 * 5;
constexpr uint32_t K_SM_TS = K_SM_INFO + 4 * STAGES + 4;
constexpr int SM_TOTAL = K_SM_TS - K_SB;
constexpr uint32_t K_SM_WQ = K_SB, K_SM_WK = K_SM_WQ + CH * CH * 2, K_SM_Q = K_SM_WK + 16 * CH * 2, K_SM_RED = K_SM_Q + 16 * CH * 2;
constexpr uint32_t K_SM_WV = K_SM_RED + 12288, K_SM_WO = K_SM_WV + CH * CH * 2;

#define SB (cb + K_SB)
#define SM_P (cb + K_SM_P)
#define SM_A (cb + K_SM_A)
#define SM_XA (cb + K_SM_XA)
#define SM_MX (cb + K_SM_MX)
#define SM_UL (cb + K_SM_UL)
#define SM_AL (cb + K_SM_AL)
#define SM_FIN (cb + K_SM_FIN)
#define SM_OW (cb + K_SM_OW)
#define SM_FW (cb + K_SM_FW)
#define SM_ZERO (cb + K_SM_ZERO)
#define SM_EP (cb + K_SM_EP)
#define SM_FLAG (cb + K_SM_FLAG)
#define BAR_FULL (cb + K_BAR_FULL)
#define BAR_EMPTY (cb + K_BAR_EMPTY)
#define BAR_W (cb + K_BAR_W)
#define BAR_EP (cb + K_BAR_EP)
#define BAR_WT (cb + K_BAR_WT)
#define BAR_V (cb + K_BAR_V)
#define BAR_JOB (cb + K_BAR_JOB)
#define SM_INFO (cb + K_SM_INFO)
#define SM_TS (cb + K_SM_TS)
#define SM_WQ (cb + K_SM_WQ)
#define SM_WK (cb + K_SM_WK)
#define SM_Q (cb + K_SM_Q)
#define SM_RED (cb + K_SM_RED)
#define SM_WV (cb + K_SM_WV)
#define SM_WO (cb + K_SM_WO)

struct __align__(128) Scratch {
    unsigned epoch, ctr, pad[30];
    unsigned flagW[128];
    uint4 qk[12 * 32];
    uint32_t wvo[3 * 4 * 12 * 128];
    uint4 M[8 * 128 * 2];
    uint4 L[8 * 128 * 2];
    uint4 T[8 * 128 * 2];
    uint4 A[8 * 64];
};
__device__ Scratch g_s;

__device__ __forceinline__ void spin_guard(unsigned it) {
    asm volatile("{\n.reg .pred p;\n.reg .b64 z;\nsetp.gt.u32 p, %0, %1;\nmov.b64 z, 0;\n@p st.global.u32 [z], %0;\n}" ::"r"(it), "n"(SPIN_LIMIT));
}
__device__ __forceinline__ uint32_t smem_u32(const void* p) { return (uint32_t)__cvta_generic_to_shared(p); }
__device__ __forceinline__ void mbar_init(uint32_t bar, int cnt) { asm volatile("mbarrier.init.shared::cta.b64 [%0], %1;" ::"r"(bar), "r"(cnt) : "memory"); }
__device__ __forceinline__ void mbar_expect_tx(uint32_t bar, uint32_t bytes) { asm volatile("mbarrier.arrive.expect_tx.shared::cta.b64 _, [%0], %1;" ::"r"(bar), "r"(bytes) : "memory"); }
__device__ __forceinline__ void mbar_arrive_if(uint32_t bar, uint32_t cond) {
    asm volatile("{\n.reg .pred p;\nsetp.ne.u32 p, %1, 0;\n@p mbarrier.arrive.shared::cta.b64 _, [%0];\n}" ::"r"(bar), "r"(cond) : "memory");
}
__device__ __forceinline__ void mbar_wait(uint32_t bar, uint32_t parity) {
    asm volatile("{\n.reg .pred p;\n.reg .u32 c;\n.reg .b64 z;\nmov.u32 c, 0;\nmov.b64 z, 0;\nbra.uni T_%=;\n"
                 "W_%=:\nadd.u32 c, c, 1;\nsetp.gt.u32 p, c, %2;\n@p st.global.u32 [z], c;\n"
                 "T_%=:\nmbarrier.try_wait.parity.shared::cta.b64 p, [%0], %1;\n@!p bra W_%=;\n}"
                 ::"r"(bar), "r"(parity), "n"(SPIN_LIMIT / 4) : "memory");
}
__device__ __forceinline__ void mbar_wait_u(uint32_t bar, uint32_t parity) {
    asm volatile("{\n.reg .pred p;\n.reg .u32 c;\n.reg .b64 z;\nmov.u32 c, 0;\nmov.b64 z, 0;\nbra.uni T_%=;\n"
                 "W_%=:\nadd.u32 c, c, 1;\nsetp.gt.u32 p, c, %2;\n@p st.global.u32 [z], c;\n"
                 "T_%=:\nmbarrier.try_wait.parity.shared::cta.b64 p, [%0], %1;\n@!p bra.uni W_%=;\n}"
                 ::"r"(bar), "r"(parity), "n"(SPIN_LIMIT / 4) : "memory");
}
__device__ __forceinline__ bool mbar_test(uint32_t bar, uint32_t parity) {
    uint32_t ok;
    asm volatile("{\n.reg .pred p;\nmbarrier.test_wait.parity.shared::cta.b64 p, [%1], %2;\nselp.u32 %0, 1, 0, p;\n}" : "=r"(ok) : "r"(bar), "r"(parity) : "memory");
    return ok != 0;
}
__device__ __forceinline__ void tma3d(uint32_t dst, const CUtensorMap* tm, int c0, int c1, int c2, uint32_t bar) {
    asm volatile("cp.async.bulk.tensor.3d.shared::cluster.global.mbarrier::complete_tx::bytes.L2::cache_hint [%0], [%1, {%3, %4, %5}], [%2], %6;"
                 ::"r"(dst), "l"(tm), "r"(bar), "r"(c0), "r"(c1), "r"(c2), "l"(EVICT_FIRST) : "memory");
}
__device__ __forceinline__ void tma2d(uint32_t dst, const CUtensorMap* tm, int c0, int c1, uint32_t bar) {
    asm volatile("cp.async.bulk.tensor.2d.shared::cluster.global.mbarrier::complete_tx::bytes.L2::cache_hint [%0], [%1, {%3, %4}], [%2], %5;"
                 ::"r"(dst), "l"(tm), "r"(bar), "r"(c0), "r"(c1), "l"(EVICT_FIRST) : "memory");
}
__device__ __forceinline__ void tma2dn(uint32_t dst, const CUtensorMap* tm, int c0, int c1, uint32_t bar) {
    asm volatile("cp.async.bulk.tensor.2d.shared::cluster.global.mbarrier::complete_tx::bytes [%0], [%1, {%3, %4}], [%2];"
                 ::"r"(dst), "l"(tm), "r"(bar), "r"(c0), "r"(c1) : "memory");
}
__device__ __forceinline__ void bulk_g2s(uint32_t dst, const void* src, uint32_t bytes, uint32_t bar) {
    asm volatile("cp.async.bulk.shared::cluster.global.mbarrier::complete_tx::bytes [%0], [%1], %2, [%3];" ::"r"(dst), "l"(src), "r"(bytes), "r"(bar) : "memory");
}
__device__ __forceinline__ void ldsm4(uint32_t a, uint32_t (&r)[4]) {
    asm volatile("ldmatrix.sync.aligned.m8n8.x4.shared.b16 {%0,%1,%2,%3}, [%4];" : "=r"(r[0]), "=r"(r[1]), "=r"(r[2]), "=r"(r[3]) : "r"(a) : "memory");
}
__device__ __forceinline__ void ldsm4t(uint32_t a, uint32_t (&r)[4]) {
    asm volatile("ldmatrix.sync.aligned.m8n8.x4.trans.shared.b16 {%0,%1,%2,%3}, [%4];" : "=r"(r[0]), "=r"(r[1]), "=r"(r[2]), "=r"(r[3]) : "r"(a) : "memory");
}
__device__ __forceinline__ void stsm4(uint32_t a, uint32_t x, uint32_t y, uint32_t z, uint32_t w) {
    asm volatile("stmatrix.sync.aligned.m8n8.x4.shared.b16 [%0], {%1,%2,%3,%4};" ::"r"(a), "r"(x), "r"(y), "r"(z), "r"(w) : "memory");
}
__device__ __forceinline__ void mma16816(float (&d)[4], uint32_t a0, uint32_t a1, uint32_t a2, uint32_t a3, uint32_t b0, uint32_t b1) {
    asm volatile("mma.sync.aligned.m16n8k16.row.col.f32.bf16.bf16.f32 {%0,%1,%2,%3}, {%4,%5,%6,%7}, {%8,%9}, {%0,%1,%2,%3};"
        : "+f"(d[0]), "+f"(d[1]), "+f"(d[2]), "+f"(d[3]) : "r"(a0), "r"(a1), "r"(a2), "r"(a3), "r"(b0), "r"(b1));
}
__device__ __forceinline__ void mma_sp(float (&d)[4], const uint32_t (&a)[4], const uint32_t (&b)[4]) {
    asm volatile("mma.sp::ordered_metadata.sync.aligned.m16n8k32.row.col.f32.bf16.bf16.f32 {%0,%1,%2,%3}, {%4,%5,%6,%7}, {%8,%9,%10,%11}, {%12,%12,%12,%12}, %13, 0x0;"
        : "=f"(d[0]), "=f"(d[1]), "=f"(d[2]), "=f"(d[3])
        : "r"(a[0]), "r"(a[1]), "r"(a[2]), "r"(a[3]), "r"(b[0]), "r"(b[1]), "r"(b[2]), "r"(b[3]), "f"(0.f), "r"(0xEEEE4444u));
}
__device__ __forceinline__ uint32_t badd2v(uint32_t a, uint32_t b) { uint32_t d; asm volatile("add.rn.bf16x2 %0, %1, %2;" : "=r"(d) : "r"(a), "r"(b)); return d; }
__device__ __forceinline__ uint32_t negv(uint32_t a) { uint32_t d; asm volatile("xor.b32 %0, %1, 0x80008000;" : "=r"(d) : "r"(a)); return d; }
__device__ __forceinline__ uint32_t pack2(float lo, float hi) { uint32_t d; asm("cvt.rn.bf16x2.f32 %0, %1, %2;" : "=r"(d) : "f"(hi), "f"(lo)); return d; }
__device__ __forceinline__ float bf_lo(uint32_t v) { return __uint_as_float(v << 16); }
__device__ __forceinline__ float bf_hi(uint32_t v) { return __uint_as_float(v & 0xffff0000u); }
__device__ __forceinline__ float ex2(float x) { float y; asm("ex2.approx.ftz.f32 %0, %1;" : "=f"(y) : "f"(x)); return y; }
__device__ __forceinline__ float rsq(float x) { float y; asm("rsqrt.approx.ftz.f32 %0, %1;" : "=f"(y) : "f"(x)); return y; }
__device__ __forceinline__ void bar_sync(int id, int n) { asm volatile("bar.sync %0, %1;" ::"r"(id), "r"(n) : "memory"); }
__device__ __forceinline__ void bar_arrive(int id, int n) { asm volatile("bar.arrive %0, %1;" ::"r"(id), "r"(n) : "memory"); }
__device__ __forceinline__ unsigned ld_acquire(const unsigned* p) { unsigned v; asm volatile("ld.acquire.gpu.global.u32 %0, [%1];" : "=r"(v) : "l"(p) : "memory"); return v; }
__device__ __forceinline__ void st_release(unsigned* p, unsigned v) { asm volatile("st.release.gpu.global.u32 [%0], %1;" ::"l"(p), "r"(v) : "memory"); }
__device__ __forceinline__ uint4 ld_relaxed4(const uint4* p) {
    uint4 v; asm volatile("ld.relaxed.gpu.global.v4.u32 {%0,%1,%2,%3}, [%4];" : "=r"(v.x), "=r"(v.y), "=r"(v.z), "=r"(v.w) : "l"(p) : "memory"); return v;
}
__device__ __forceinline__ void ld_relaxed4_if(uint4& v, const uint4* p, uint32_t cond) {
    asm volatile("{\n.reg .pred p;\nsetp.ne.u32 p, %5, 0;\n@p ld.relaxed.gpu.global.v4.u32 {%0,%1,%2,%3}, [%4];\n}"
                 : "+r"(v.x), "+r"(v.y), "+r"(v.z), "+r"(v.w) : "l"(p), "r"(cond) : "memory");
}
__device__ __forceinline__ uint32_t collect(const uint4* tp, uint32_t par, uint32_t on) {
    uint32_t t;
    asm volatile("{\n.reg .pred p, q, r;\n.reg .b32 u, c;\n.reg .b64 z;\nmov.b32 c, 0;\nmov.b64 z, 0;\nmov.b32 %0, 0;\nsetp.ne.u32 r, %3, 0;\n"
                 "L_%=:\n@r ld.relaxed.gpu.global.u32 %0, [%1];\nadd.u32 c, c, 1;\nsetp.gt.u32 q, c, %4;\n@q st.global.u32 [z], c;\n"
                 "lop3.b32 u, %0, %2, %3, 0x28;\nsetp.ne.u32 p, u, 0;\nvote.sync.any.pred p, p, -1;\n@p bra.uni L_%=;\n}"
                 : "=&r"(t) : "l"(tp), "r"(par), "r"(on), "n"(SPIN_LIMIT) : "memory");
    return t;
}
__device__ __forceinline__ void load_at(float2& v, uint32_t on, uint32_t tl, const float2* p, uint32_t id) {
    asm volatile("{\n.reg .pred q, r;\n.reg .b32 t0, t1;\n.reg .b64 g;\n"
                 "A_%=:\nmov.u64 g, %%globaltimer;\ncvt.u32.u64 t0, g;\nsub.u32 t0, t0, %3;\nsetp.lt.s32 q, t0, 0;\n@q bra.uni A_%=;\n"
                 "prmt.b32 t1, %2, t0, %5;\n"
                 "prmt.b32 t1, t1, t1, %5;\n"
                 "prmt.b32 t1, t1, t1, %5;\n"
                 "setp.ne.u32 r, t1, 0;\n@r ld.relaxed.gpu.global.v2.f32 {%0,%1}, [%4];\n}"
                 : "+f"(v.x), "+f"(v.y) : "r"(on), "r"(tl), "l"(p), "r"(id) : "memory");
}
__device__ __forceinline__ void st_async_if(uint32_t dst, uint32_t a, uint32_t b, uint32_t c, uint32_t d, uint32_t bar, uint32_t cond) {
    asm volatile("{\n.reg .pred p;\nsetp.ne.u32 p, %6, 0;\n@p st.async.weak.shared::cluster.mbarrier::complete_tx::bytes.v4.b32 [%0], {%1,%2,%3,%4}, [%5];\n}"
                 ::"r"(dst), "r"(a), "r"(b), "r"(c), "r"(d), "r"(bar), "r"(cond) : "memory");
}
__device__ __forceinline__ void red_if(__nv_bfloat16* p, uint32_t a, uint32_t b, uint32_t c, uint32_t d, bool cond) {
    asm volatile("{\n.reg .pred p;\nsetp.ne.u32 p, %5, 0;\n@p red.global.add.noftz.v4.bf16x2 [%0], {%1,%2,%3,%4};\n}"
                 ::"l"(p), "r"(a), "r"(b), "r"(c), "r"(d), "r"((uint32_t)cond) : "memory");
}
__device__ __forceinline__ uint32_t mapa(uint32_t a, uint32_t rank) { uint32_t d; asm volatile("mapa.shared::cluster.u32 %0, %1, %2;" : "=r"(d) : "r"(a), "r"(rank)); return d; }
__device__ __forceinline__ uint32_t f2uv(float x) { uint32_t r; asm volatile("cvt.rzi.u32.f32 %0, %1;" : "=r"(r) : "f"(x)); return r; }
__device__ __forceinline__ void sts16(uint32_t a, uint32_t x) { asm volatile("{\n.reg .b16 h;\ncvt.u16.u32 h, %1;\nst.shared.u16 [%0], h;\n}" ::"r"(a), "r"(x) : "memory"); }
__device__ __forceinline__ void st_v4(uint4* p, uint32_t a, uint32_t b, uint32_t c, uint32_t d) {
    asm volatile("st.relaxed.gpu.global.v4.u32 [%0], {%1,%2,%3,%4};" ::"l"(p), "r"(a), "r"(b), "r"(c), "r"(d) : "memory");
}
__device__ __forceinline__ void st_v4_if(uint4* p, uint32_t a, uint32_t b, uint32_t c, uint32_t d, bool cond) {
    asm volatile("{\n.reg .pred p;\nsetp.ne.u32 p, %5, 0;\n@p st.relaxed.gpu.global.v4.u32 [%0], {%1,%2,%3,%4};\n}"
                 ::"l"(p), "r"(a), "r"(b), "r"(c), "r"(d), "r"((uint32_t)cond) : "memory");
}
__device__ __forceinline__ uint32_t pack2t(float lo, float hi, uint32_t par) {
    return (__byte_perm(__float_as_uint(lo) + ((par ^ 1u) << 16), pack2(0.f, hi), 0x7632) & ~1u) | par;
}
__device__ __forceinline__ void lds128(uint32_t a, uint32_t (&r)[4]) {
    asm volatile("ld.shared.v4.u32 {%0,%1,%2,%3}, [%4];" : "=r"(r[0]), "=r"(r[1]), "=r"(r[2]), "=r"(r[3]) : "r"(a) : "memory");
}
__device__ __forceinline__ float sum4(const uint32_t (&r)[4]) {
    return (__uint_as_float(r[0]) + __uint_as_float(r[1])) + (__uint_as_float(r[2]) + __uint_as_float(r[3]));
}
__device__ __forceinline__ void sts32(uint32_t a, uint32_t x) { asm volatile("st.shared.u32 [%0], %1;" ::"r"(a), "r"(x) : "memory"); }
__device__ __forceinline__ void stsf(uint32_t a, float x) { asm volatile("st.shared.f32 [%0], %1;" ::"r"(a), "f"(x) : "memory"); }
__device__ __forceinline__ void stsf2(uint32_t a, float x, float y) { asm volatile("st.shared.v2.f32 [%0], {%1,%2};" ::"r"(a), "f"(x), "f"(y) : "memory"); }
__device__ __forceinline__ float ldsf(uint32_t a) { float v; asm volatile("ld.shared.f32 %0, [%1];" : "=f"(v) : "r"(a) : "memory"); return v; }
__device__ __forceinline__ float2 ldsf2(uint32_t a) { float2 v; asm volatile("ld.shared.v2.f32 {%0,%1}, [%2];" : "=f"(v.x), "=f"(v.y) : "r"(a) : "memory"); return v; }
__device__ __forceinline__ uint32_t lds32(uint32_t a) { uint32_t v; asm volatile("ld.shared.u32 %0, [%1];" : "=r"(v) : "r"(a) : "memory"); return v; }
__device__ __forceinline__ uint32_t ldsv32(uint32_t a) { uint32_t v; asm volatile("ld.volatile.shared.u32 %0, [%1];" : "=r"(v) : "r"(a) : "memory"); return v; }
__device__ __forceinline__ float warp_max(float x) {
    int k = __float_as_int(x);
    k = __reduce_max_sync(0xffffffffu, k ^ ((k >> 31) & 0x7fffffff));
    return __int_as_float(k ^ ((k >> 31) & 0x7fffffff));
}
__device__ __forceinline__ uint32_t now_ns() { uint32_t t; asm volatile("mov.u32 %0, %globaltimer_lo;" : "=r"(t) :: "memory"); return t; }
__device__ __forceinline__ uint32_t clk32() { uint32_t t; asm volatile("mov.u32 %0, %clock;" : "=r"(t) :: "memory"); return t; }
__device__ __forceinline__ void sched_fence(uint32_t& sink) { uint64_t t; asm volatile("mov.u64 %0, %clock64;" : "=l"(t) :: "memory"); sink ^= (uint32_t)(t >> 32); }
__device__ __forceinline__ void sink_if(uint32_t addr, uint32_t sink, uint32_t cond) {
    asm volatile("{\n.reg .pred p;\nsetp.ne.u32 p, %2, 0;\n@p st.shared.u32 [%0], %1;\n}" ::"r"(addr), "r"(sink), "r"(cond) : "memory");
}
__device__ __forceinline__ uint32_t opaque(uint32_t v, int lane) { return __shfl_sync(0xffffffffu, v, lane); }

__device__ __forceinline__ void el_arrive(uint32_t bar) {
    asm volatile("{\n.reg .pred p;\nelect.sync _|p, -1;\n@p mbarrier.arrive.shared::cta.b64 _, [%0];\n}" ::"r"(bar) : "memory");
}
__device__ __forceinline__ void el_expect_tx(uint32_t bar, uint32_t bytes) {
    asm volatile("{\n.reg .pred p;\nelect.sync _|p, -1;\n@p mbarrier.arrive.expect_tx.shared::cta.b64 _, [%0], %1;\n}" ::"r"(bar), "r"(bytes) : "memory");
}
__device__ __forceinline__ void el_tile(uint32_t cb, int s, int t, const CUtensorMap* tm0, const CUtensorMap* tm1) {
    asm volatile("{\n.reg .pred p;\nelect.sync _|p, -1;\n"
                 "@p cp.async.bulk.tensor.3d.shared::cluster.global.mbarrier::complete_tx::bytes.L2::cache_hint [%0], [%1, {%9, %4, %5}], [%3], %7;\n"
                 "@p cp.async.bulk.tensor.2d.shared::cluster.global.mbarrier::complete_tx::bytes.L2::cache_hint [%8], [%2, {%9, %6}], [%3], %7;\n}"
                 ::"r"(SB + s * STAGE_BYTES), "l"(tm0), "l"(tm1), "r"(BAR_FULL + 8 * s), "r"((t & 15) * 96), "r"((t >> 4) * 2), "r"(t * 48),
                   "l"(EVICT_FIRST), "r"(SB + s * STAGE_BYTES + 24576), "r"(0) : "memory");
}
__device__ __forceinline__ void el_bulk(uint32_t dst, const void* src, uint32_t bytes, uint32_t bar) {
    asm volatile("{\n.reg .pred p;\nelect.sync _|p, -1;\n"
                 "@p cp.async.bulk.shared::cluster.global.mbarrier::complete_tx::bytes [%0], [%1], %2, [%3];\n}" ::"r"(dst), "l"(src), "r"(bytes), "r"(bar) : "memory");
}
__device__ __forceinline__ void issue_tile(uint32_t cb, int s, int t, const CUtensorMap* tm0, const CUtensorMap* tm1) {
    const uint32_t bar = BAR_FULL + 8 * s;
    mbar_expect_tx(bar, STAGE_BYTES);
    tma3d(SB + s * STAGE_BYTES, tm0, 0, (t & 15) * 96, (t >> 4) * 2, bar);
    tma2d(SB + s * STAGE_BYTES + 24576, tm1, 0, t * 48, bar);
}

__global__ void __cluster_dims__(CL, 1, 1) __launch_bounds__(384, 1)
fused_kernel(uint64_t scn  , const __nv_bfloat16* __restrict__ q,
             const char* f0, const char* f1, const char* wq, const char* wk,
             const __grid_constant__ CUtensorMap tm0, const __grid_constant__ CUtensorMap tm1,
             const __grid_constant__ CUtensorMap tmq, const __grid_constant__ CUtensorMap tmk,
             const __grid_constant__ CUtensorMap tmv, const __grid_constant__ CUtensorMap tmo,
             __nv_bfloat16* __restrict__ out, const uint4* scl) {
    extern __shared__ __align__(1024) char smem_raw[];
    const int tid = threadIdx.x, warp = tid >> 5, lane = tid & 31;
    const int bid = blockIdx.x, e0 = bid - NSERV;
    const uint32_t cb0 = smem_u32(smem_raw) - K_SB;

    Scratch* const sc = reinterpret_cast<Scratch*>(scn & ~(uint64_t)127);
    [[maybe_unused]] const uint32_t cb = cb0;
    const int NS = ((int)scn & 127) + 1;
    const int NE = NS - NSERV, src = bid;
    int ticket = 0;
    asm volatile("{\n.reg .pred p, s;\n.reg .b32 a, b;\n.reg .b64 x, y;\nsetp.ne.u32 p, %8, 256;\nsetp.lt.s32 s, %9, 0;\n@p bra N_%=;\n@s bra.uni V_%=;\n"
                 "and.b32 a, %9, -16;\nadd.u32 a, a, %9;\nmad.wide.u32 x, a, 12288, %1;\nmad.wide.u32 y, %9, 6144, %2;\n"
                 "cp.async.bulk.prefetch.L2.global.L2::cache_hint [x], 12288, %6;\ncp.async.bulk.prefetch.L2.global.L2::cache_hint [y], 6144, %6;\n"
                 "cp.async.bulk.prefetch.L2.global.L2::cache_hint [x+196608], 12288, %6;\n"
                 "bra E_%=;\n"
                 "V_%=:\nadd.u32 b, %9, %10;\nmad.wide.u32 x, b, 512, %5;\ncp.async.bulk.prefetch.L2.global [x], 512;\n"
                 "mad.wide.u32 x, b, 6144, %4;\ncp.async.bulk.prefetch.L2.global [x], 6144;\n"
                 "mad.wide.u32 y, b, 6144, %3;\ncp.async.bulk.prefetch.L2.global [y], 6144;\nbra E_%=;\n"
                 "N_%=:\nsetp.eq.u32 p, %8, 288;\n@p ld.relaxed.gpu.global.u32 %0, [%7];\nE_%=:\n}"
                 : "+r"(ticket) : "l"(f0), "l"(f1), "l"(wq), "l"(wk), "l"(q), "l"(EVICT_FIRST), "l"(&sc->epoch), "r"(tid), "r"(e0), "n"(NSERV) : "memory");
    if (tid == 320) {
        mbar_init(BAR_FULL, 2);
        if (e0 >= 0) {
            issue_tile(cb, 0, e0, &tm0, &tm1);
        } else {
#pragma unroll
            for (int i = 0; i < 5; ++i) mbar_init(BAR_JOB + 8 * i, 1);
            mbar_expect_tx(BAR_JOB, 32 * CH * 2);
            bulk_g2s(SM_Q, q, 16 * CH * 2, BAR_JOB);
            tma2dn(SM_WK, &tmk, 0, bid * 48, BAR_JOB);
#pragma unroll
            for (int c = 0; c < 3; ++c) {
                mbar_expect_tx(BAR_JOB + 8 + 8 * c, 64 * CH * 2);
                tma2dn(SM_WQ + c * 64 * CH * 2, &tmq, 0, c * 192, BAR_JOB + 8 + 8 * c);
            }
        }
    } else if (tid == 0) {
#pragma unroll
        for (int i = 1; i < 2 * STAGES + 6; ++i)
            mbar_init(BAR_FULL + 8 * i, i < STAGES ? 2 : 1);
#pragma unroll
        for (int e = 0; e < 3; ++e) mbar_expect_tx(BAR_V + 8 * e, CL * 256);
        asm volatile("fence.mbarrier_init.release.cluster;" ::: "memory");
    } else if (warp == 1) {
        stsf2(SM_ZERO + lane * 8, 0.f, 0.f);
        if (lane < 4) stsf2(SM_EP + lane * 8, 0.f, 0.f);
        if (lane <= STAGES) sts32(SM_INFO + 4 * lane, lane == STAGES - 1);
        spin_guard((smem_u32(smem_raw) & 0xffffffu) == K_SB ? 0u : ~0u);
    }
    __syncthreads();
    if (warp != 11) asm volatile("barrier.cluster.arrive.relaxed.aligned;" ::: "memory");

    const int g = lane >> 2, j = lane & 3, m4 = lane >> 3, r8 = lane & 7;

    if (e0 < 0) {
        if (tid == 320) {
            mbar_expect_tx(BAR_JOB + 32, (CH + 16) * CH * 2);
            tma2dn(SM_WO, &tmo, bid * 16, 0, BAR_JOB + 32);
#pragma unroll
            for (int c = 0; c < 3; ++c) tma2dn(SM_WV + c * 64 * CH * 2, &tmv, 0, c * 192, BAR_JOB + 32);
        }
        if (tid == 288) sts32(SM_EP, ticket + 1);
        if (warp == 9) st_v4(&sc->qk[bid * 32 + lane], __shfl_sync(0xffffffffu, ticket, 0), 0u, 0u, 0u);
        st_v4_if(reinterpret_cast<uint4*>(sc->flagW) + bid * 2 + (tid & 1), 0u, 0u, 0u, 0u, tid < 2);
        __syncwarp();
        mbar_wait(BAR_JOB, 0);
        if (warp == 10) {
            uint32_t t[4];
            lds128(SM_Q + bid * 512 + lane * 16, t);
            st_v4(reinterpret_cast<uint4*>(out) + bid * 32 + lane, t[0], t[1], t[2], t[3]);
            st_v4_if(&sc->A[(bid & 7) * 64 + (lane & 7)], 0u, 0u, 0u, 0u, bid < 8 && lane < 8);
        }
        if (warp < 8) {
            const int row = 2 * warp + (lane >> 4), c0 = (lane & 15) * 8;
            float v[3][4];
#pragma unroll
            for (int c = 0; c < 3; ++c) {
                const float2 t = ldsf2(SM_Q + row * 384 + c * 128 + c0);
                v[c][0] = bf_lo(__float_as_uint(t.x)); v[c][1] = bf_hi(__float_as_uint(t.x));
                v[c][2] = bf_lo(__float_as_uint(t.y)); v[c][3] = bf_hi(__float_as_uint(t.y));
            }
            float sum = ((v[0][0] + v[0][1]) + (v[0][2] + v[0][3])) + ((v[1][0] + v[1][1]) + (v[1][2] + v[1][3])) + ((v[2][0] + v[2][1]) + (v[2][2] + v[2][3]));
#pragma unroll
            for (int d = 1; d < 16; d <<= 1) sum += __shfl_xor_sync(0xffffffffu, sum, d);
            const float mean = sum * (1.f / CH);
            float ss[3];
#pragma unroll
            for (int c = 0; c < 3; ++c) {
#pragma unroll
                for (int e = 0; e < 4; ++e) v[c][e] -= mean;
                ss[c] = fmaf(v[c][0], v[c][0], v[c][1] * v[c][1]) + fmaf(v[c][2], v[c][2], v[c][3] * v[c][3]);
            }
            sum = ss[0] + ss[1] + ss[2];
#pragma unroll
            for (int d = 1; d < 16; d <<= 1) sum += __shfl_xor_sync(0xffffffffu, sum, d);
            const float rstd = rsq(sum * (1.f / CH) + LN_EPS);
#pragma unroll
            for (int c = 0; c < 3; ++c)
                stsf2(SM_A + row * 400 + c * 128 + c0, __uint_as_float(pack2(v[c][0] * rstd, v[c][1] * rstd)), __uint_as_float(pack2(v[c][2] * rstd, v[c][3] * rstd)));
        }
        {
            float d[2][2][4];
#pragma unroll
            for (int c = 0; c < 4; ++c) d[0][0][c] = d[0][1][c] = d[1][0][c] = d[1][1][c] = 0.f;
            uint32_t a[12][4], qa[4];
#pragma unroll
            for (int k = 0; k < 12; ++k) {
                const int r = 3 * ((m4 & 1) * 8 + r8) + (k >> 2);
                ldsm4(SM_WK + r * 128 + ((((k & 3) * 2 + (m4 >> 1)) ^ (r & 7)) << 4), a[k]);
            }
            mbar_wait(BAR_JOB + 8 + 8 * (warp >> 2), 0);
#pragma unroll
            for (int k = 0; k < 12; ++k) {
                uint32_t b[4];
                const int r = 3 * ((m4 >> 1) * 8 + r8) + (k >> 2);
                ldsm4(SM_WQ + warp * 6144 + r * 128 + ((((k & 3) * 2 + (m4 & 1)) ^ (r & 7)) << 4), b);
                mma16816(d[0][k & 1], a[k][0], a[k][1], a[k][2], a[k][3], b[0], b[1]);
                mma16816(d[1][k & 1], a[k][0], a[k][1], a[k][2], a[k][3], b[2], b[3]);
            }
            bar_sync(1, 384);
            ldsm4(SM_A + ((m4 & 1) * 8 + r8) * 400 + (16 * warp + (m4 >> 1) * 8) * 2, qa);
#pragma unroll
            for (int nb = 0; nb < 2; ++nb) {
                uint32_t hi[2], lo[2];
#pragma unroll
                for (int t = 0; t < 2; ++t) {
                    const float v0 = d[t][0][2 * nb] + d[t][1][2 * nb], v1 = d[t][0][2 * nb + 1] + d[t][1][2 * nb + 1];
                    hi[t] = pack2(v0, v1);
                    lo[t] = pack2(v0 - bf_lo(hi[t]), v1 - bf_hi(hi[t]));
                }
                float e[4] = {0.f, 0.f, 0.f, 0.f};
                mma16816(e, qa[0], qa[1], qa[2], qa[3], hi[0], hi[1]);
                mma16816(e, qa[0], qa[1], qa[2], qa[3], lo[0], lo[1]);
                stsm4(SM_RED + (warp * 2 + nb) * 512 + lane * 16, __float_as_uint(e[0]), __float_as_uint(e[1]), __float_as_uint(e[2]), __float_as_uint(e[3]));
            }
            bar_sync(1, 384);
            if (warp == 0) {
                float r[8] = {0.f, 0.f, 0.f, 0.f, 0.f, 0.f, 0.f, 0.f};
#pragma unroll
                for (int u = 0; u < 24; ++u) {
                    uint32_t e[4];
                    ldsm4(SM_RED + u * 512 + lane * 16, e);
#pragma unroll
                    for (int c = 0; c < 4; ++c) r[(u & 1) * 4 + c] += __uint_as_float(e[c]);
                }
                const float qs = 1.4426950408889634f * 13.856406460551018f;
                const uint32_t a0 = pack2t(r[0] * qs, r[1] * qs, lds32(SM_EP) & 1u), a1 = pack2(r[2] * qs, r[3] * qs);
                const uint32_t a2 = pack2(r[4] * qs, r[5] * qs), a3 = pack2(r[6] * qs, r[7] * qs);
                st_v4(&sc->qk[bid * 32 + lane], a0, a1, a2, a3);
            }
        }
        {
            mbar_wait(BAR_JOB + 32, 0);
            float d[2][4] = {{0.f, 0.f, 0.f, 0.f}, {0.f, 0.f, 0.f, 0.f}};
#pragma unroll 1
            for (int k = 0; k < 12; ++k) {
                uint32_t a[4], b[4];
                ldsm4t(SM_WO + (16 * k + (m4 >> 1) * 8 + r8) * 32 + (m4 & 1) * 16, a);
                const int r = 3 * ((m4 >> 1) * 8 + r8) + (k >> 2);
                ldsm4(SM_WV + warp * 6144 + r * 128 + ((((k & 3) * 2 + (m4 & 1)) ^ (r & 7)) << 4), b);
                mma16816(d[0], a[0], a[1], a[2], a[3], b[0], b[1]);
                mma16816(d[1], a[0], a[1], a[2], a[3], b[2], b[3]);
            }
            float s0 = (d[0][0] + d[0][1]) + (d[1][0] + d[1][1]), s1 = (d[0][2] + d[0][3]) + (d[1][2] + d[1][3]);
            s0 += __shfl_xor_sync(0xffffffffu, s0, 1); s1 += __shfl_xor_sync(0xffffffffu, s1, 1);
            s0 += __shfl_xor_sync(0xffffffffu, s0, 2); s1 += __shfl_xor_sync(0xffffffffu, s1, 2);
            if (j == 0) stsf2(SM_FW + (warp * 8 + g) * 8, s0, s1);
            bar_sync(1, 384);
            s0 = s1 = 0.f;
#pragma unroll 1
            for (int u = 0; u < 12; ++u) { const float2 t = ldsf2(SM_FW + (u * 8 + g) * 8); s0 += t.x; s1 += t.y; }
            s0 *= 1.f / CH; s1 *= 1.f / CH;
            const int h = bid / 3, i = (warp + 12 - 3 * h) % 12;
            uint32_t* wp = &sc->wvo[(((i >> 2) * 4 + h) * 12 + (i & 3) * 3 + bid % 3) * 128 + lane];
            wp[0] = pack2(d[0][0] - s0, d[0][1] - s0); wp[32] = pack2(d[1][0] - s0, d[1][1] - s0);
            wp[64] = pack2(d[0][2] - s1, d[0][3] - s1); wp[96] = pack2(d[1][2] - s1, d[1][3] - s1);
            asm volatile("fence.proxy.async;" ::: "memory");
            bar_sync(1, 384);
            if (tid == 0) st_release(&sc->flagW[bid * 8], lds32(SM_EP));
        }
    }

    if (warp < 4) {
        asm volatile("setmaxnreg.inc.sync.aligned.u32 176;");
        const uint32_t cb = opaque(cb0, lane);
        const int w = warp;
        uint32_t oa[6], ob[6];
#pragma unroll
        for (int b = 0; b < 3; ++b) {
            int r = 3 * (8 * w + r8) + b;
            uint32_t o = SB + r * 128 + ((m4 ^ (r & 7)) << 4);
            oa[2 * b] = opaque(o, lane); oa[2 * b + 1] = opaque(o ^ 64u, lane);
            r = 3 * (4 * w + (r8 >> 1)) + b;
            o = SB + 24576 + r * 128 + ((m4 ^ 1 ^ (r & 7)) << 4);
            ob[2 * b] = opaque(o, lane); ob[2 * b + 1] = opaque(o ^ 64u, lane);
        }
        uint32_t one[4][2];
#pragma unroll
        for (int i = 0; i < 4; ++i) {
            one[i][0] = 0x3F803F80u + lds32(SM_ZERO + (lane + 2 * i) * 4); one[i][1] = 0x3F803F80u + lds32(SM_ZERO + (lane + 2 * i + 1) * 4);
        }
        const uint32_t dmask = opaque(j == (g >> 1) ? 0xffff0000u : 0u, lane);
        const float dsel = __uint_as_float(opaque(j == (g >> 1) ? 0x3f800000u : 0u, lane));
        const bool odd = opaque(g & 1, lane) != 0;
        uint32_t first = 0;
        const uint32_t pst = opaque(SM_P + w * 512 + lane * 16, lane);
        const uint32_t lst = opaque(SM_UL + 256 + (j & 1) * 128 + g * 16 + w * 4, lane), loff = opaque(((g * 128 + src) * 2 + (j & 1)) * 16, lane);
        const bool odj = lst & 128;
        uint32_t qk[12][4];
#pragma unroll
        for (int k = 0; k < 12; ++k) qk[k][0] = qk[k][1] = qk[k][2] = qk[k][3] = 0u;
        float R0 = 0.f, R1 = 0.f;
        float m0 = -INFINITY, m1 = -INFINITY, l0 = 0.f, l1 = 0.f;
        int s = STAGES - 1; uint32_t st = (STAGES - 1) * STAGE_BYTES, ph = 1, pbuf = 0;
        uint32_t sink = lds32(SM_ZERO + (lane + 8) * 4), seq = 0;
        mbar_wait(BAR_EP, 0);
#pragma unroll 1
        while (true) {
            mbar_wait(BAR_FULL + 8 * s, ph);
            uint32_t r0[6][4], r1[6][4], f[6][4];
            float S2[2][2][4], T2[2][2][4];
#pragma unroll
            for (int b = 0; b < 2; ++b)
#pragma unroll
                for (int c = 0; c < 4; ++c) { S2[0][b][c] = S2[1][b][c] = 0.f; T2[0][b][c] = T2[1][b][c] = 0.f; }
            uint32_t d0[2][2], d1[2][2];
#pragma unroll
            for (int n = 0; n < 2; ++n) { ldsm4(st + ob[n], f[n]); ldsm4(st + oa[n], r0[n]); ldsm4(st + oa[n] + 12288, r1[n]); }
            sched_fence(sink);
#pragma unroll
            for (int k = -1; k < 12; ++k) {
                const int n = (k + 1) / 2 + 2;
                if (n < 6) {
                    if ((k + 1) & 1) ldsm4(st + oa[n] + 12288, r1[n]);
                    else { ldsm4(st + ob[n], f[n]); ldsm4(st + oa[n], r0[n]); }
                }
                if (k == ORDER_AT) bar_arrive(8, 256);
                if (k >= 0) {
                    const int i = k >> 1, h = k & 1;
                    mma16816(T2[h][0], d0[h][0], one[h][0], d0[h][1], one[h][1], r0[i][2 * h], r0[i][2 * h + 1]);
                    mma16816(T2[h][1], d1[h][0], one[2 + h][0], d1[h][1], one[2 + h][1], r1[i][2 * h], r1[i][2 * h + 1]);
                    mma16816(S2[h][0], qk[k][0], qk[k][1], qk[k][2], qk[k][3], r0[i][2 * h], r0[i][2 * h + 1]);
                    mma16816(S2[h][1], qk[k][0], qk[k][1], qk[k][2], qk[k][3], r1[i][2 * h], r1[i][2 * h + 1]);
                }
                if (k < 11) {
                    const int i = (k + 1) >> 1, h = (k + 1) & 1;
#pragma unroll
                    for (int c = 0; c < 2; ++c) {
                        r0[i][2 * h + c] = badd2v(r0[i][2 * h + c], f[i][2 * h + (c ^ 1)]); r1[i][2 * h + c] = badd2v(r1[i][2 * h + c], f[i][2 * h + (c ^ 1)]);
                        d0[h][c] = negv(r0[i][2 * h + c]); d1[h][c] = negv(r1[i][2 * h + c]);
                    }
                    sched_fence(sink);
                }
            }
            float S[2][4], T[2][4];
#pragma unroll
            for (int b = 0; b < 2; ++b)
#pragma unroll
                for (int c = 0; c < 4; ++c) { S[b][c] = S2[0][b][c] + S2[1][b][c]; T[b][c] = T2[0][b][c] + T2[1][b][c]; }
            uint32_t rb[2];
#pragma unroll
            for (int b = 0; b < 2; ++b) {
                const float qd = odd ? T[b][1] : T[b][0], sd = odd ? T[b][3] : T[b][2];
                const float rd = rsq(fmaxf(fmaf(qd, -(float)CH, fmaf(-sd, sd, EPS2)), EPS2));
                const float hi = __uint_as_float(__float_as_uint(rd) & dmask);
                rb[b] = pack2(fmaf(rd, dsel, -hi), hi);
            }
            float rs[4] = {0.f, 0.f, 0.f, 0.f};
            mma16816(rs, 0x3F803F80u, 0u, 0u, 0x3F803F80u, rb[0], rb[1]);
            float y[2][4], z[2][4], p[2][4];
            uint32_t pp[4];
#pragma unroll
            for (int b = 0; b < 2; ++b) {
                y[b][0] = fmaf(-T[b][2], R0, S[b][0]); y[b][1] = fmaf(-T[b][3], R0, S[b][1]);
                y[b][2] = fmaf(-T[b][2], R1, S[b][2]); y[b][3] = fmaf(-T[b][3], R1, S[b][3]);
            }
            auto softmax_p = [&](uint32_t pb) {
#pragma unroll
                for (int b = 0; b < 2; ++b) {
                    z[b][0] = fmaf(rs[2 * b], y[b][0], -m0); z[b][1] = fmaf(rs[2 * b + 1], y[b][1], -m0);
                    z[b][2] = fmaf(rs[2 * b], y[b][2], -m1); z[b][3] = fmaf(rs[2 * b + 1], y[b][3], -m1);
#pragma unroll
                    for (int c = 0; c < 4; ++c) p[b][c] = ex2(z[b][c]);
                    pp[2 * b] = pack2(p[b][0] * rs[2 * b], p[b][1] * rs[2 * b + 1]);
                    pp[2 * b + 1] = pack2(p[b][2] * rs[2 * b], p[b][3] * rs[2 * b + 1]);
                }
                stsm4(pst + pb, pp[0], pp[1], pp[2], pp[3]);
            };
            softmax_p(pbuf);
            const float zmax = fmaxf(fmaxf(fmaxf(z[0][0], z[0][1]), fmaxf(z[0][2], z[0][3])), fmaxf(fmaxf(z[1][0], z[1][1]), fmaxf(z[1][2], z[1][3])));
            ++seq;
            sink_if(SM_FLAG + (pbuf >> 9), seq, zmax > RESCALE_TH);
            const uint32_t info = lds32(SM_INFO + 4 * s);
            bar_sync(1, 256);
            const float k0 = l0, k1 = l1;
            l0 += (p[0][0] + p[0][1]) + (p[1][0] + p[1][1]);
            l1 += (p[0][2] + p[0][3]) + (p[1][2] + p[1][3]);
            const uint32_t flag = lds32(SM_FLAG + (pbuf >> 9));
            mbar_arrive_if(BAR_EMPTY + 8 * s, first);
            pbuf ^= 2048;
            st += STAGE_BYTES;
            if (++s == STAGES) { s = 0; st = 0; ph ^= 1; }
            auto hand_over = [&](uint32_t fl) {
                const float e = (odj ? l1 : l0) + __shfl_xor_sync(0xffffffffu, odj ? l0 : l1, 1);
                const uint32_t ow = ldsv32(SM_OW + (loff >> 12) * 4);
                const float2 pub = ldsf2(SM_OW + 32 + (loff >> 12) * 8);
                const float e2 = __shfl_xor_sync(0xffffffffu, e, 2);
                float cnt = m0 == pub.x && m1 == pub.y && ow != ~0u ? 1.f : 2049.f, wt = odj ? bf_hi(ow) : bf_lo(ow);
                const char* ap = reinterpret_cast<const char*>(sc->A) + (loff >> 12 << 10) + ((loff & 16) >> 1);
                uint32_t on = seq != 1 && !(pst & 32);
                asm volatile("" : "+f"(cnt), "+f"(wt), "+l"(ap), "+r"(on));
                const float tot = e + e2;
                asm volatile("{\n.reg .pred p, q;\n.reg .f32 v;\nmul.f32 v, %1, %2;\nsetp.ne.u32 q, %5, %6;\nsetp.ne.and.u32 p, %4, 0, q;\n"
                             "@p red.relaxed.gpu.global.add.v2.f32 [%0], {v, %3};\n}"
                             ::"l"(ap), "f"(tot), "f"(wt), "f"(cnt), "r"(on), "r"(fl), "r"(seq) : "memory");
                sched_fence(sink);
                stsf(lst, tot * (1.f / CH));
            };
            if (info & 1) {
                hand_over(flag);
                if (info == 1 && flag != seq) goto publish;
            }
            if (flag != seq && !(info & 3)) continue;
            if (flag == seq) {
                const int tz = tid + lds32(SM_EP + 4), w = tz >> 5, g = tz >> 2 & 7, j = tz & 3;
                float x0 = fmaxf(fmaxf(rs[0] * y[0][0], rs[1] * y[0][1]), fmaxf(rs[2] * y[1][0], rs[3] * y[1][1]));
                float x1 = fmaxf(fmaxf(rs[0] * y[0][2], rs[1] * y[0][3]), fmaxf(rs[2] * y[1][2], rs[3] * y[1][3]));
                x0 = fmaxf(x0, __shfl_xor_sync(0xffffffffu, x0, 1)); x0 = fmaxf(x0, __shfl_xor_sync(0xffffffffu, x0, 2));
                x1 = fmaxf(x1, __shfl_xor_sync(0xffffffffu, x1, 1)); x1 = fmaxf(x1, __shfl_xor_sync(0xffffffffu, x1, 2));
                stsf(SM_MX + (w * 16 + g + (j & 1) * 8) * 4, (j & 1) ? x1 : x0);
                bar_sync(2, 128);
                float n0 = m0, n1 = m1;
#pragma unroll
                for (int u = 0; u < 4; ++u) { n0 = fmaxf(n0, ldsf(SM_MX + (u * 16 + g) * 4)); n1 = fmaxf(n1, ldsf(SM_MX + (u * 16 + g + 8) * 4)); }
                n0 = ceilf(n0); n1 = ceilf(n1);
                n0 = __uint_as_float((__float_as_uint(n0) + (n0 > 0.f ? __float_as_uint(n0) & 1u : 0u)) & ~1u);
                const float a0 = ex2(m0 - n0), a1 = ex2(m1 - n1);
                m0 = n0; m1 = n1;
                stsf(SM_AL + j * 32 + g * 4, j == 0 ? a0 : j == 1 ? a1 : j == 2 ? n0 : n1);
                bar_arrive(3, 256);
                softmax_p(pbuf ^ 2048);
                bar_sync(1, 256);
                l0 = fmaf(k0, a0, (p[0][0] + p[0][1]) + (p[1][0] + p[1][1]));
                l1 = fmaf(k1, a1, (p[0][2] + p[0][3]) + (p[1][2] + p[1][3]));
                if (info & 1) hand_over(0);
            }
            if (info & 2) {
                s += 3; st += 3 * STAGE_BYTES;
                if (s >= STAGES) { s -= STAGES; st -= STAGES * STAGE_BYTES; ph ^= 1; }
            }
            if (!(info & 1)) continue;
        publish:
            asm volatile("{\n.reg .pred p;\nsetp.ne.u32 p, %0, 0;\n@p bar.arrive 2, 128;\n@p exit;\n}" ::"r"((uint32_t)(seq != 1 && w != 0)) : "memory");
            const uint32_t epoch = lds32(SM_EP);
            uint32_t lsa = lst & ~140u;
            asm volatile("" : "+r"(lsa));
            bar_sync(2, 128);
            {
                uint32_t la[4], lb[4];
                lds128(lsa, la); lds128(lsa + 128, lb);
                const float sa = sum4(la), sb = sum4(lb);
                const uint32_t mt = __float_as_uint(m0) | ((epoch ^ (seq == 1)) & 1u);
                const float ha = __uint_as_float(__float_as_uint(sa) & 0xffff0000u), hb = __uint_as_float(__float_as_uint(sb) & 0xffff0000u);
                st_v4(reinterpret_cast<uint4*>(reinterpret_cast<char*>(sc->L) + loff), pack2(ha, sa - ha), pack2(hb, sb - hb), mt, __float_as_uint(m1));
            }
            if (seq != 1) return;
            sink_if(SM_EP + 8, sink, lds32(SM_EP + 4));
            m0 = m1 = -INFINITY; l0 = l1 = 0.f;
            const int tz = tid + lds32(SM_EP + 4), w = tz >> 5, lane = tz & 31;
            uint4 v[3];
            unsigned it = 0;
            while (true) {
                if (it < 2 && src >= NSERV) mbar_wait(BAR_FULL + 8 * (QK_AFTER + it), 0);
#pragma unroll
                for (int k = 0; k < 3; ++k) v[k] = ld_relaxed4(&sc->qk[(3 * w + k) * 32 + lane]);
                const uint32_t bad = (v[0].x ^ epoch) | (v[1].x ^ epoch) | (v[2].x ^ epoch);
                if (__all_sync(0xffffffffu, (bad & 1u) == 0)) break;
                spin_guard(++it);
            }
            bar_sync(6, 256);
#pragma unroll
            for (int k = 0; k < 3; ++k) stsm4(SM_XA + (3 * w + k) * 512 + lane * 16, v[k].x, v[k].y, v[k].z, v[k].w);
            bar_sync(2, 128);
#pragma unroll
            for (int k = 0; k < 12; ++k) ldsm4(SM_XA + k * 512 + lane * 16, qk[k]);
            asm volatile("fence.proxy.async.shared::cta;" ::: "memory");
            bar_sync(2, 128);
            mbar_arrive_if(BAR_EMPTY + 8 * (STAGES - 1), tz == 0);
            first = tz == 0;
            float r[4] = {0.f, 0.f, 0.f, 0.f}, r2[4] = {0.f, 0.f, 0.f, 0.f};
#pragma unroll
            for (int k = 0; k < 12; k += 2) {
                mma16816(r, qk[k][0], qk[k][1], qk[k][2], qk[k][3], 0x3F803F80u, 0x3F803F80u);
                mma16816(r2, qk[k + 1][0], qk[k + 1][1], qk[k + 1][2], qk[k + 1][3], 0x3F803F80u, 0x3F803F80u);
            }
            R0 = (r[0] + r2[0]) * (1.f / CH); R1 = (r[2] + r2[2]) * (1.f / CH);
        }
    } else if (warp < 8) {
        asm volatile("setmaxnreg.inc.sync.aligned.u32 256;");
        const uint32_t cb = opaque(cb0, lane);
        pad<4>();
        const int h = __shfl_sync(0xffffffffu, warp - 4, 0);
        uint32_t oa[3], ob[3];
#pragma unroll
        for (int b = 0; b < 3; ++b) {
            int cc = 6 * h + 2 * b + (m4 >> 1);
            int r = 3 * r8 + (cc >> 3);
            oa[b] = opaque(SB + (m4 & 1) * 12288 + r * 128 + (((cc & 7) ^ (r & 7)) << 4), lane);
            cc = 6 * h + 2 * b + (m4 & 1);
            r = 3 * (4 * (m4 >> 1) + (r8 >> 1)) + (cc >> 3);
            ob[b] = opaque(SB + 24576 + r * 128 + (((cc & 7) ^ (r & 7)) << 4), lane);
        }
        const uint32_t l16 = opaque(lane * 16, lane);
        const uint32_t vdst = opaque(mapa(SM_A + (bid & (CL - 1)) * 832 + h * 192 + ((j ^ (bid >> 1 & 3)) << 4), g), lane), vbar = opaque(mapa(BAR_V, g), lane);
        uint32_t axb = SM_XA;
        float acc[6][4];
#pragma unroll
        for (int t = 0; t < 6; ++t) acc[t][0] = acc[t][1] = acc[t][2] = acc[t][3] = 0.f;
        int s = STAGES - 1; uint32_t ph = 1, pbuf = 0;
        uint32_t wf[12][3][4];
#pragma unroll
        for (int i = 0; i < 12; ++i)
#pragma unroll
            for (int c = 0; c < 4; ++c) wf[i][0][c] = wf[i][1][c] = wf[i][2][c] = 0u;
        uint32_t seq = 0, info = 0, sink = 0;
        mbar_wait(BAR_EP, 0);
        uint32_t par = ~lds32(SM_EP) & 1u;
        st_v4_if(&sc->M[(g * 128 + src) * 2 + (j & 1)], 0u, 0u, par, 0u, ((j & 2) | h) == 0);
#pragma unroll 1
        while (true) {
            if (info & 8) {
                const uint32_t lz = l16 + lds32(SM_EP + 4);
                const uint32_t pub0 = lds32(SM_AL + 64 + (lz >> 6 << 2)), pub1 = lds32(SM_AL + 96 + (lz >> 6 << 2));
                if (h == 0) stsf2(SM_OW + 32 + (lz >> 6 << 3), __uint_as_float(pub0), __uint_as_float(pub1));
                st_v4_if(&sc->M[((lz >> 6) * 128 + src) * 2 + (lz >> 4 & 1)], 0u, 0u, pub0 | par, pub1, ((lz & 32) | h) == 0);
            }
            if (info & 2) {
                const uint32_t lz = l16 + lds32(SM_EP + 4);
                asm volatile("barrier.cluster.wait.aligned;" ::: "memory");
#pragma unroll
                for (int c = 0; c < 3; ++c) {
                    mbar_wait(BAR_FULL + 8 * s, ph);
#pragma unroll
                    for (int i = 0; i < 12; ++i) ldsm4(SB + s * STAGE_BYTES + (h * 12 + i) * 512 + lz, wf[4 * c + i / 3][i % 3]);
                    bar_sync(4, 128);
                    mbar_arrive_if(BAR_EMPTY + 8 * s, (lz | h) == 0);
                    if (++s == STAGES) { s = 0; ph ^= 1; }
                }
            }
            if (info & 4) {
                float u0 = 0.f, u1 = 0.f;
#pragma unroll
                for (int t = 0; t < 6; ++t) { u0 += acc[t][0] + acc[t][1]; u1 += acc[t][2] + acc[t][3]; }
                const uint32_t lz = l16 + lds32(SM_EP + 4);
                const bool j1 = lz & 16;
                const float e = (j1 ? u1 : u0) + __shfl_xor_sync(0xffffffffu, j1 ? u0 : u1, 1);
                stsf(SM_UL + (lz & 16) * 8 + (lz >> 6 << 4) + h * 4, (e + __shfl_xor_sync(0xffffffffu, e, 2)) * (1.f / CH));
                bar_sync(4, 128);
                uint32_t ua[4], ub[4];
                lds128(SM_UL + (lz >> 6 << 4), ua); lds128(SM_UL + 128 + (lz >> 6 << 4), ub);
                u0 = sum4(ua); u1 = sum4(ub);
#pragma unroll
                for (int t = 0; t < 6; ++t) { acc[t][0] -= u0; acc[t][1] -= u0; acc[t][2] -= u1; acc[t][3] -= u1; }
            }
            auto project = [&]() {
                uint32_t af[12][4], ax[4];
#pragma unroll
                for (int i = 0; i < 4; ++i) ax[i] = axb + ((h + i) & 3) * 1536;
                const uint32_t real = seq != 1;
#pragma unroll
                for (int ks = 0; ks < 3; ++ks) {
                    af[ks][0] = pack2(acc[2 * ks][0], acc[2 * ks][1]); af[ks][1] = pack2(acc[2 * ks][2], acc[2 * ks][3]);
                    af[ks][2] = pack2(acc[2 * ks + 1][0], acc[2 * ks + 1][1]); af[ks][3] = pack2(acc[2 * ks + 1][2], acc[2 * ks + 1][3]);
                    stsm4(ax[0] + ks * 512 + l16, af[ks][0], af[ks][1], af[ks][2], af[ks][3]);
                }
                float o[4][2][4];
                constexpr int ord[36] = {0,1,2,0,1,2,0,1,2, 0,1,0,2,0,1,0,1,0,2,0,1,0,1,0,1,0, 1,2,1,2,1, 2,3,2,3,2};
                int nx[3] = {0, 0, 0};
                bool used3 = false;
#pragma unroll
                for (int z = 0; z < 36; ++z) {
                    const int a = ord[z], tp = a == 3 ? 2 : a, i = nx[tp]++;
                    if (i == 0 || (a == 3 && !used3)) {
#pragma unroll
                        for (int c = 0; c < 4; ++c) o[a][0][c] = o[a][1][c] = 0.f;
                    }
                    if (a == 3) used3 = true;
                    mma16816(o[a][0], af[i][0], af[i][1], af[i][2], af[i][3], wf[i][tp][0], wf[i][tp][1]);
                    mma16816(o[a][1], af[i][0], af[i][1], af[i][2], af[i][3], wf[i][tp][2], wf[i][tp][3]);
                    if (z == 0 || z == 2 || z == 30) sched_fence(sink);
                    if (z == 2) bar_sync(4, 128);
                    if (z == REL_Z) asm volatile("{\n.reg .pred p;\nsetp.ne.u32 p, %0, 0;\n@p bar.arrive 12, 256;\n}" ::"r"(real) : "memory");
#pragma unroll
                    for (int k = 0; k < 9; ++k) if (z == 2) ldsm4(ax[1 + k / 3] + (k % 3) * 512 + l16, af[3 + k]);
#pragma unroll
                    for (int e = 0; e < 3; ++e)
                        if (z == (e == 0 ? 26 : e == 1 ? 31 : 35)) {
                            if (e == 2) {
#pragma unroll
                                for (int c = 0; c < 4; ++c) { o[2][0][c] += o[3][0][c]; o[2][1][c] += o[3][1][c]; }
                            }
                            st_async_if(vdst + e * 64, pack2(o[e][0][0], o[e][0][1]), pack2(o[e][1][0], o[e][1][1]),
                                        pack2(o[e][0][2], o[e][0][3]), pack2(o[e][1][2], o[e][1][3]), vbar + 8 * e, real);
                        }
                }
            };
            if (!(info & 1)) {
                const uint32_t st = __shfl_sync(0xffffffffu, s * STAGE_BYTES, 0);
                axb = SB + st;
                const uint32_t lz = l16 + lds32(SM_EP + 4);
                const char* tp = reinterpret_cast<const char*>(sc->T) + ((lz >> 5 << 12) + (lz & 16) + src * 32);
                uint32_t ann = (lz >> 8 | h) == 0;
                asm volatile("" : "+l"(tp), "+r"(ann));
                mbar_wait(BAR_FULL + 8 * s, ph);
                asm volatile("{\n.reg .pred p;\n.reg .b32 t, u;\nld.shared.u32 %0, [%1];\nmov.u32 t, %%globaltimer_lo;\nlop3.b32 t, t, 1, %3, 0xba;\n"
                             "and.b32 u, %0, %4;\nsetp.ne.u32 p, u, 0;\n@p st.relaxed.gpu.global.v4.u32 [%2], {t,t,t,t};\n}"
                             : "=r"(info) : "r"(SM_INFO + 4 * s), "l"(tp), "r"(par), "r"(ann) : "memory");
                bar_sync(8, 256);
                uint32_t xt[4][3][4];
#pragma unroll
                for (int u = 0; u < 6; ++u) {
                    const int gp = u / 3, b = u % 3;
                    if (u == 5) asm volatile("{\n.reg .pred p;\nsetp.ne.u32 p, %0, 0;\n@p bar.arrive 11, 256;\n}" ::"r"((uint32_t)((info & 1) && seq != 0)) : "memory");
                    uint32_t f[4];
                    ldsm4t(st + ob[b] + gp * 3072, f);
                    ldsm4t(st + oa[b] + (2 * gp) * 3072, xt[2 * gp][b]);
                    ldsm4t(st + oa[b] + (2 * gp + 1) * 3072, xt[2 * gp + 1][b]);
                    if (u == 1 || u == 3) sched_fence(sink);
#pragma unroll
                    for (int c = 0; c < 4; ++c) {
                        xt[2 * gp][b][c] = badd2v(xt[2 * gp][b][c], f[c >> 1]);
                        xt[2 * gp + 1][b][c] = badd2v(xt[2 * gp + 1][b][c], f[2 + (c >> 1)]);
                    }
                }
                ++seq;
                const uint32_t pb = pbuf;
                pbuf ^= 2048;
                if (++s == STAGES) { s = 0; ph ^= 1; }
                auto accumulate = [&]() {
                    uint32_t pa[4][4], fa = SM_FLAG + (pb >> 9);
#pragma unroll 1
                    while (true) {
                        if (fa == SM_EP + 4) {
                            bar_sync(3, 256);
                            const uint32_t gz = (l16 + lds32(SM_EP + 4)) >> 6 << 2;
                            const float a0 = ldsf(SM_AL + gz), a1 = ldsf(SM_AL + 32 + gz);
#pragma unroll
                            for (int t = 0; t < 6; ++t) { acc[t][0] *= a0; acc[t][1] *= a0; acc[t][2] *= a1; acc[t][3] *= a1; }
                        }
                        bar_sync(1, 256);
                        uint32_t flag;
                        asm volatile("ld.shared.u32 %4, [%6];\nldmatrix.sync.aligned.m8n8.x4.shared.b16 {%0,%1,%2,%3}, [%5];"
                                     : "=r"(pa[0][0]), "=r"(pa[0][1]), "=r"(pa[0][2]), "=r"(pa[0][3]), "=r"(flag) : "r"(SM_P + l16 + pb), "r"(fa) : "memory");
                        fa = SM_EP + 4;
                        if (flag != seq) break;
                    }
#pragma unroll
                    for (int gq = 1; gq < 4; ++gq) ldsm4(SM_P + l16 + pb + gq * 512, pa[gq]);
#pragma unroll
                    for (int gq = 0; gq < 4; ++gq)
#pragma unroll
                        for (int b = 0; b < 3; ++b) {
                            mma16816(acc[2 * b], pa[gq][0], pa[gq][1], pa[gq][2], pa[gq][3], xt[gq][b][0], xt[gq][b][1]);
                            mma16816(acc[2 * b + 1], pa[gq][0], pa[gq][1], pa[gq][2], pa[gq][3], xt[gq][b][2], xt[gq][b][3]);
                        }
                };
                if (info != 1) { accumulate(); continue; }
                accumulate();
                project();
            } else {
                project();
            }
            if (seq != 1) break;
            sink_if(SM_EP + 8, sink, lds32(SM_EP + 4));
            asm volatile("fence.proxy.async.shared::cta;" ::: "memory");
            bar_arrive(6, 256);
            par ^= 1u;
            info = 0;
#pragma unroll
            for (int t = 0; t < 6; ++t) acc[t][0] = acc[t][1] = acc[t][2] = acc[t][3] = 0.f;
        }
    } else {
        asm volatile("setmaxnreg.dec.sync.aligned.u32 72;");
        const uint32_t cb = opaque(cb0, lane);
        const int fw = __shfl_sync(0xffffffffu, warp - 8, 0);
        if (fw == 0) {
            if (src < NSERV) {
                el_expect_tx(BAR_FULL, STAGE_BYTES);
                el_tile(cb, 0, JOIN_N * NE + src, &tm0, &tm1);
            }
            el_expect_tx(BAR_FULL + 8, STAGE_BYTES);
            el_tile(cb, 1, src < NSERV ? JOIN_N * NE + NS + src : src - NSERV + NE, &tm0, &tm1);
            el_arrive(BAR_FULL);
        } else if (fw == 1) {
            const unsigned epoch = __shfl_sync(0xffffffffu, ticket + 1, 0);
            sts32(SM_EP, epoch);
            el_arrive(BAR_EP);
            stsf2(SM_FLAG + 8, __uint_as_float(now_ns()), __uint_as_float(clk32()));
            __nanosleep(6000);
            unsigned it = 0;
            while (!__all_sync(0xffffffffu, ld_acquire(sc->flagW + min(lane, NSERV - 1) * 8) == epoch)) { spin_guard(++it); __nanosleep(64); }
            asm volatile("fence.proxy.async;" ::: "memory");
            __syncwarp();
            el_arrive(BAR_W);
        } else if (fw == 3) {
            if (lane < CL) sts32(SM_OW + 4 * lane, ~0u);
            asm volatile("barrier.cluster.arrive.relaxed.aligned;" ::: "memory");
        }
        uint32_t sink = 0;
        int slot = 2, n = fw ? 0 : src < NSERV ? JOIN_N + 2 : 2, sp = 1, sd = 0;
        uint32_t pp = 0, pd = 0;
#pragma unroll 1
        for (int real = 0; ; ++real) {
        {
            const int wat = CHECKPOINT + (bid & WSTAG), pause = real ? 0 : PAUSE + (bid >> 4 & 7);
            auto wait_empty = [&](int sl) {
                const int r = (sl * 37) >> 8, st = sl - r * STAGES;
                mbar_wait_u(BAR_EMPTY + 8 * st, (r ^ (st != STAGES - 1)) & 1);
                return st;
            };
            while (n != pause && n != 0) {
                const int t = n < JOIN_N ? src - NSERV + n * NE : n < NSTATIC ? src + n * NS - JOIN_N * NSERV : NSTATIC * NS - JOIN_N * NSERV + __shfl_sync(0xffffffffu, ticket, 0);
                const bool done = t >= NTILES, winj = n == wat || (done && n < wat);
                sts32(SM_INFO + 4 * sp, done + 2 * winj + 4 * ((unsigned)(NTILES - END_X - t) < (unsigned)(2 * NS)) + 8 * (n == MX_AT || (done && n < MX_AT)));
                sts32(SM_INFO + 4 * STAGES, done ? ~0u : n);
                el_arrive(BAR_FULL + 8 * sp);
                const int wslot = slot;
                if (winj) slot += 3;
                if (!done) {
                    const int s = wait_empty(slot);
                    el_expect_tx(BAR_FULL + 8 * s, STAGE_BYTES);
                    mbar_wait_u(BAR_FULL + 8 * sd, pd);
                    if (n >= MID_FROM || t >= NTILES - END_X) {
                        const uint32_t c0 = clk32(), hold = t >= NTILES - END_X ? D_END : MID_D;
                        while (clk32() - c0 < hold && !mbar_test(BAR_FULL + 8 * sp, pp)) __nanosleep(50);
                    }
                    asm volatile("{\n.reg .pred p;\nsetp.ne.u32 p, %2, 0;\n@p atom.relaxed.gpu.global.inc.u32 %0, [%1], 0x7fffffff;\n}"
                                 : "+r"(ticket) : "l"(&sc->ctr), "r"((uint32_t)(n >= NSTATIC - 1 && lane == 0)) : "memory");
                    el_tile(cb, s, t, &tm0, &tm1);
                    sd = sp; pd = pp; sp = s; pp = ((slot * 37) >> 8) & 1;
                    ++n;
                    if (++slot >= 2 * STAGES) slot -= 2 * STAGES;
                } else {
                    n = 0;
                }
                if (winj) {
                    mbar_wait_u(BAR_W, 0);
#pragma unroll 1
                    for (int c = 0; c < 3; ++c) {
                        const int st = wait_empty(wslot + c);
                        el_expect_tx(BAR_FULL + 8 * st, 24576);
                        el_bulk(SB + st * STAGE_BYTES, sc->wvo + c * 6144, 24576, BAR_FULL + 8 * st);
                        el_arrive(BAR_FULL + 8 * st);
                    }
                }
            }
        }
        if (fw == 0) bar_arrive(7, 128);
        {
            const int ft = tid - 256 + lds32(SM_EP + 4), lane = ft & 31, g = lane >> 2, j = lane & 3;
            const int n0 = src & (CL - 1);
            const uint32_t epoch = lds32(SM_EP), par = epoch & 1u;
            unsigned it = 0;
            if (fw == 1 && real) {
                const uint4* xp = &(real > 1 ? sc->L : sc->M)[(n0 * 128 + lane) * 2];
                uint4 x[4];
                while ((uint32_t)ldsv32(SM_INFO + 4 * STAGES) < WT_AT) { __nanosleep(1000); spin_guard(++it); }
                while (true) {
#pragma unroll
                    for (int i = 0; i < 4; ++i) {
                        x[i] = make_uint4(0u, 0u, 0xff7ffffeu | par, 0xff7fffffu);
                        ld_relaxed4_if(x[i], xp + 64 * i, 32 * i + lane < NS);
                    }
                    if (!__any_sync(0xffffffffu, ((x[0].z ^ par) | (x[1].z ^ par) | (x[2].z ^ par) | (x[3].z ^ par)) & 1u)) break;
                    if (real == 1) __nanosleep(1000);
                    spin_guard(++it);
                }
#pragma unroll
                for (int i = 0; i < 4; ++i) x[i].z &= ~1u;
                const float Xa = warp_max(fmaxf(fmaxf(__uint_as_float(x[0].z), __uint_as_float(x[1].z)), fmaxf(__uint_as_float(x[2].z), __uint_as_float(x[3].z))));
                const float Xb = warp_max(fmaxf(fmaxf(__uint_as_float(x[0].w), __uint_as_float(x[1].w)), fmaxf(__uint_as_float(x[2].w), __uint_as_float(x[3].w))));
                uint32_t own = 0;
#pragma unroll
                for (int i = 0; i < 4; ++i) {
                    const uint32_t w2 = pack2(ex2(__uint_as_float(x[i].z) - Xa), ex2(__uint_as_float(x[i].w) - Xb));
                    if (i == src >> 5) own = w2;
                    sts16(SM_FW + (32 * i + lane) * 2, w2); sts16(SM_FW + 272 + (32 * i + lane) * 2, w2 >> 16);
                }
                __syncwarp();
                el_arrive(BAR_WT);
                if (real == 1) {
                    asm volatile("barrier.cluster.wait.aligned;" ::: "memory");
                    asm volatile("{\n.reg .pred p;\nsetp.ne.u32 p, %2, 0;\n@p st.relaxed.cluster.shared::cluster.u32 [%0], %1;\n}"
                                 ::"r"(mapa(SM_OW + n0 * 4, lane & (CL - 1))), "r"(own), "r"((uint32_t)(((lane ^ src) >> 3 & 3) == 0)) : "memory");
                }
            }
            const uint32_t valid = real && 32 * fw + lane < NS;
            const uint4* lp = scl + (n0 * 128 + min(32 * fw + lane, NS - 1)) * 2;
            sched_fence(sink);
            if (fw) bar_sync(7, 128);
            else mbar_wait_u(real ? BAR_WT : BAR_EP, real ? ~real & 1 : 0);
            uint32_t av = lds32(SM_FW + (g & 1) * 272 + (src & ~(CL - 1)) * 2 + j * 4);
            asm volatile("mul.rn.bf16x2 %0, %0, %1;" : "+r"(av) : "r"(0x43404340u));
            const float2 ts = ldsf2(SM_FLAG + 8);
            uint32_t t0 = __float_as_uint(ts.x);
            const float nspc = fminf(__fdividef((float)(now_ns() - t0), (float)(clk32() - __float_as_uint(ts.y))), 2.f);
            uint32_t llag = t0 + MEMNS + f2uv(nspc * LLAG);
            uint32_t vsrc = SM_A + (lane & 7) * 832 + fw * 192 + (((lane >> 3) ^ (lane >> 1 & 3)) << 4), vb = real ? BAR_V : BAR_EP, vbs = real ? 8 : 0;
            uint32_t id = 0x3210 + lds32(SM_EP + 4), chk = valid ? ~0u : 0u, on = real == 1;
            uint32_t wr = real && (g & 1) == (j >> 1) ? g >> 1 : 3, epw = real;
            __nv_bfloat16* op = out + (n0 + (j >> 1) * 8) * CH + 48 * fw + 8 * (j & 1) + 16 * (g >> 1);
            const float2* ap = reinterpret_cast<const float2*>(&sc->A[n0 * 64]) + (j >> 1);
            float want = real ? (float)(4 * NS) : 0.f;
            uint32_t aq[4] = {av, lds32(SM_ZERO + lane * 4), lds32(SM_ZERO + 128 + lane * 4), av + lds32(SM_EP + 4)};
            asm volatile("" : "+l"(lp), "+l"(op), "+l"(ap), "+r"(vsrc), "+r"(vb), "+r"(vbs), "+r"(chk), "+r"(wr), "+r"(id), "+r"(on), "+r"(epw), "+f"(want), "+r"(llag), "+r"(t0));
            sched_fence(sink);
            if (real == 1) bar_sync(11, 256);
            {
                sts32(SM_FIN + fw * 4, __reduce_max_sync(0xffffffffu, (collect(lp + 8 * 128 * 2, par, on) - t0) & (on ? chk : 0u)));
                bar_sync(13, 128);
                uint32_t t4[4];
                lds128(SM_FIN, t4);
                llag += max(max(t4[0], t4[1]), max(t4[2], t4[3]));
                asm volatile("{\n.reg .pred p;\nsetp.eq.u32 p, %2, 0;\n@p st.global.v2.u32 [%0], {%1, %2};\n}" ::"l"(&sc->epoch), "r"(epoch), "r"(src | fw | lane | !on) : "memory");
            }
            if (real == 1) bar_sync(12, 256);
            float2 la = make_float2(1.f, 0.f);
            load_at(la, on, llag, ap, id);
            float r[8];
            auto part = [&](int e) {
                uint32_t bv[4];
                mbar_wait_u(vb + e * vbs, 0);
                ldsm4t(vsrc + e * 64, bv);
#pragma unroll
                for (int u = 0; u < 2; ++u) {
                    float c[4] = {0.f, 0.f, 0.f, 0.f};
                    mma16816(c, aq[0], aq[1], aq[2], aq[3], bv[2 * u], bv[2 * u + 1]);
#pragma unroll
                    for (int i = 0; i < 4; ++i) r[4 * u + i] = e == 0 || wr == e ? c[i] : r[4 * u + i];
                }
                asm volatile("" : "+f"(r[0]), "+f"(r[1]), "+f"(r[2]), "+f"(r[3]), "+f"(r[4]), "+f"(r[5]), "+f"(r[6]), "+f"(r[7]));
            };
            part(0);
            part(1);
            part(2);
            sched_fence(sink);
            asm volatile("{\n.reg .pred p, q;\n.reg .f32 i, t<8>;\n.reg .b32 a, b, c, d;\n"
                         "rcp.approx.ftz.f32 i, %0;\nsetp.eq.f32 q, %1, %2;\nsetp.lt.and.u32 p, %11, 3, q;\n"
                         "mul.f32 t0, %3, i;\nmul.f32 t1, %4, i;\nmul.f32 t2, %5, i;\nmul.f32 t3, %6, i;\n"
                         "mul.f32 t4, %7, i;\nmul.f32 t5, %8, i;\nmul.f32 t6, %9, i;\nmul.f32 t7, %10, i;\n"
                         "cvt.rn.bf16x2.f32 a, t1, t0;\ncvt.rn.bf16x2.f32 b, t3, t2;\ncvt.rn.bf16x2.f32 c, t5, t4;\ncvt.rn.bf16x2.f32 d, t7, t6;\n"
                         "@p red.global.add.noftz.v4.bf16x2 [%12], {a, b, c, d};\n"
                         "setp.ne.and.u32 p, %13, 0, q;\n@p exit;\n"
                         "}"
                         ::"f"(la.x), "f"(la.y), "f"(want), "f"(r[0]), "f"(r[1]), "f"(r[2]), "f"(r[3]), "f"(r[4]), "f"(r[5]), "f"(r[6]), "f"(r[7]),
                           "r"(wr), "l"(op), "r"(epw) : "memory");
            sink ^= (aq[0] ^ aq[1]) + (aq[2] ^ aq[3]);
            uint32_t redo = 0;
            if (la.y != want) {
                float L;
                if (real == 1) {
                    while ((f2uv(la.y) & 2047u) != (unsigned)(4 * NS)) {
                        asm volatile("ld.relaxed.gpu.global.v2.f32 {%0,%1}, [%2];" : "=f"(la.x), "=f"(la.y) : "l"(ap) : "memory");
                        spin_guard(++it);
                    }
                    redo = la.y != want;
                    L = la.x;
                } else {
                    const int lz = lane + lds32(SM_EP + 4), gz = lz >> 2, jz = lz & 3;
                    uint32_t wa[4], b[4];
                    const float2 x = ldsf2(SM_FW + (gz & 1) * 272 + fw * 64 + jz * 8), y = ldsf2(SM_FW + (gz & 1) * 272 + fw * 64 + 32 + jz * 8);
                    wa[0] = __float_as_uint(x.x); wa[1] = __float_as_uint(x.y); wa[2] = __float_as_uint(y.x); wa[3] = __float_as_uint(y.y);
                    const uint32_t ldst = SB + (fw * 32 + lz) * 16;
                    uint4 l = make_uint4(0u, 0u, 0u, 0u);
                    ld_relaxed4_if(l, lp, chk);
                    asm volatile("st.shared.v4.u32 [%0], {%1,%2,%3,%4};" ::"r"(ldst), "r"(l.x), "r"(l.y), "r"(l.z), "r"(l.w) : "memory");
                    __syncwarp();
                    ldsm4t(ldst, b);
                    float c[4];
                    mma_sp(c, wa, b);
                    asm volatile("{\n.reg .pred p;\nsetp.ne.u32 p, %2, 0;\n@p st.shared.f32 [%0], %1;\n}"
                                 ::"r"(SM_FIN + 32 + (lz == 5) * 16 + fw * 4), "f"((c[0] + c[2]) + (c[1] + c[3])), "r"((uint32_t)(lz == 0 || lz == 5)) : "memory");
                    bar_sync(13, 128);
                    uint32_t d[4];
                    lds128(SM_FIN + 32 + (jz >> 1) * 16, d);
                    L = sum4(d) * (float)CH;
                }
                float inv;
                asm volatile("rcp.approx.ftz.f32 %0, %1;" : "=f"(inv) : "f"(L));
                red_if(op, pack2(r[0] * inv, r[1] * inv), pack2(r[2] * inv, r[3] * inv), pack2(r[4] * inv, r[5] * inv), pack2(r[6] * inv, r[7] * inv), !redo && wr < 3);
            }
            if (real && !redo) return;
            sink_if(SM_EP + 8, sink, lds32(SM_EP + 4));
            bar_sync(9, 128);
            spin_guard(real);
        }
        }
    }
}

typedef CUresult (*EncodeFn)(CUtensorMap*, CUtensorMapDataType, cuuint32_t, void*, const cuuint64_t*, const cuuint64_t*,
                             const cuuint32_t*, const cuuint32_t*, CUtensorMapInterleave, CUtensorMapSwizzle,
                             CUtensorMapL2promotion, CUtensorMapFloatOOBfill);

}

extern "C" void kernel_launch(void* const* d_in, const int* in_sizes, int n_in, void* d_out, int out_size) {
    (void)in_sizes; (void)n_in; (void)out_size;
    static EncodeFn enc = nullptr;
    static int grid = 0;
    static Scratch* scratch = nullptr;
    if (!enc) {
        cudaDriverEntryPointQueryResult qr;
        cudaGetDriverEntryPoint("cuTensorMapEncodeTiled", (void**)&enc, cudaEnableDefault, &qr);
        cudaGetSymbolAddress((void**)&scratch, g_s);
        int dev = 0, sms = 0;
        cudaGetDevice(&dev);
        cudaDeviceGetAttribute(&sms, cudaDevAttrMultiProcessorCount, dev);
        (void)sms;
        cudaFuncSetAttribute(fused_kernel, cudaFuncAttributeMaxDynamicSharedMemorySize, SM_TOTAL);
        cudaLaunchConfig_t cfg = {};
        cfg.gridDim = dim3(MAXS); cfg.blockDim = dim3(384); cfg.dynamicSmemBytes = SM_TOTAL;
        cudaLaunchAttribute at[1]; at[0].id = cudaLaunchAttributeClusterDimension; at[0].val.clusterDim.x = CL; at[0].val.clusterDim.y = 1; at[0].val.clusterDim.z = 1;
        cfg.attrs = at; cfg.numAttrs = 1;
        int ncl = 0;
        cudaOccupancyMaxActiveClusters(&ncl, fused_kernel, &cfg);
        grid = (ncl < MAXS / CL ? ncl : MAXS / CL) * CL;
    }
    CUtensorMap tm0, tm1, tmq, tmk, tmv, tmo;
    {
        cuuint64_t gd[3] = {64, 1536, 512}; cuuint64_t gs[2] = {128, 196608};
        cuuint32_t bd[3] = {64, 96, 2}; cuuint32_t es[3] = {1, 1, 1};
        enc(&tm0, CU_TENSOR_MAP_DATA_TYPE_BFLOAT16, 3, d_in[1], gd, gs, bd, es, CU_TENSOR_MAP_INTERLEAVE_NONE,
            CU_TENSOR_MAP_SWIZZLE_128B, CU_TENSOR_MAP_L2_PROMOTION_L2_64B, CU_TENSOR_MAP_FLOAT_OOB_FILL_NONE);
    }
    auto map2d = [&](CUtensorMap* tm, void* p, cuuint64_t cols, cuuint64_t rows, cuuint32_t bc, cuuint32_t br, CUtensorMapSwizzle sw) {
        cuuint64_t gd[2] = {cols, rows}; cuuint64_t gs[1] = {cols * 2};
        cuuint32_t bd[2] = {bc, br}; cuuint32_t es[2] = {1, 1};
        enc(tm, CU_TENSOR_MAP_DATA_TYPE_BFLOAT16, 2, p, gd, gs, bd, es, CU_TENSOR_MAP_INTERLEAVE_NONE,
            sw, CU_TENSOR_MAP_L2_PROMOTION_L2_64B, CU_TENSOR_MAP_FLOAT_OOB_FILL_NONE);
    };
    map2d(&tm1, d_in[2], 64, 196608, 64, 48, CU_TENSOR_MAP_SWIZZLE_128B);
    map2d(&tmq, d_in[3], 64, 576, 64, 192, CU_TENSOR_MAP_SWIZZLE_128B);
    map2d(&tmk, d_in[4], 64, 576, 64, 48, CU_TENSOR_MAP_SWIZZLE_128B);
    map2d(&tmv, d_in[5], 64, 576, 64, 192, CU_TENSOR_MAP_SWIZZLE_128B);
    map2d(&tmo, d_in[6], 192, 192, 16, 192, CU_TENSOR_MAP_SWIZZLE_NONE);
    fused_kernel<<<grid, 384, SM_TOTAL>>>((uint64_t)scratch | (grid - 1), (const __nv_bfloat16*)d_in[0], (const char*)d_in[1], (const char*)d_in[2],
                                          (const char*)d_in[3], (const char*)d_in[4], tm0, tm1, tmq, tmk, tmv, tmo, (__nv_bfloat16*)d_out, scratch->L);
}
```

```cpp
#include <cuda_runtime.h>
#include <cuda.h>
#include <cuda_bf16.h>
#include <stdint.h>

namespace {

constexpr int CH = 192;
constexpr int NTILES = 4096;
constexpr int STAGES = 7;
constexpr int STAGE_BYTES = 30720;
constexpr int NSERV = 12;
constexpr int CL = 8;
constexpr int MAXS = 128;
constexpr float LN_EPS = 1e-5f;
constexpr float EPS2 = LN_EPS * CH * CH;
constexpr float RESCALE_TH = 60.0f;
#define NSTATIC 6
#define JOIN_N 3
static_assert(NSTATIC >= JOIN_N + 3, "a service CTA starts with two static tiles and requests its first ticket with the third one");
#define ORDER_AT 7
#define CHECKPOINT 10
#define WSTAG 15
#define MX_AT 9
#define WT_AT (MX_AT + 6)
#define PAUSE 12
#define D_END 1085
#define END_X 240
#define MID_D 675
#define MID_FROM 16
#define QK_AFTER 3
#define MEMNS 164
#define LLAG 920
#define REL_Z 18
template <int N> __device__ __forceinline__ void pad() { if constexpr (N > 0) { asm volatile("pmevent 1;"); pad<N - 1>(); } }
constexpr unsigned SPIN_LIMIT = 1u << 22;
constexpr uint64_t EVICT_FIRST = 0x12F0000000000000ull;

constexpr uint32_t K_SB = 1024;
constexpr uint32_t K_SM_P = K_SB + STAGES * STAGE_BYTES;
constexpr uint32_t K_SM_A = K_SM_P + 4096;
constexpr uint32_t K_SM_XA = K_SB + (STAGES - 1) * STAGE_BYTES;
constexpr uint32_t K_SM_MX = K_SM_A + 6656;
constexpr uint32_t K_SM_UL = K_SM_MX + 256;
constexpr uint32_t K_SM_AL = K_SM_UL + 512;
constexpr uint32_t K_SM_FIN = K_SM_AL + 128;
constexpr uint32_t K_SM_OW = K_SM_FIN + 64;
constexpr uint32_t K_SM_FW = K_SM_OW + 128;
constexpr uint32_t K_SM_ZERO = K_SM_FW + 768;
constexpr uint32_t K_SM_EP = K_SM_ZERO + 256;
constexpr uint32_t K_SM_FLAG = K_SM_EP + 16;
constexpr uint32_t K_BAR_FULL = K_SM_FLAG + 16, K_BAR_EMPTY = K_BAR_FULL + 8 * STAGES, K_BAR_W = K_BAR_EMPTY + 8 * STAGES;
constexpr uint32_t K_BAR_EP = K_BAR_W + 8;
constexpr uint32_t K_BAR_WT = K_BAR_EP + 8;
constexpr uint32_t K_BAR_V = K_BAR_WT + 8;
constexpr uint32_t K_BAR_JOB = K_BAR_V + 24;
constexpr uint32_t K_SM_INFO = K_BAR_JOB + 8 * 5;
constexpr uint32_t K_SM_TS = K_SM_INFO + 4 * STAGES + 4;
constexpr int SM_TOTAL = K_SM_TS - K_SB;
constexpr uint32_t K_SM_WQ = K_SB, K_SM_WK = K_SM_WQ + CH * CH * 2, K_SM_Q = K_SM_WK + 16 * CH * 2, K_SM_RED = K_SM_Q + 16 * CH * 2;
constexpr uint32_t K_SM_WV = K_SM_RED + 12288, K_SM_WO = K_SM_WV + CH * CH * 2;

#define SB (cb + K_SB)
#define SM_P (cb + K_SM_P)
#define SM_A (cb + K_SM_A)
#define SM_XA (cb + K_SM_XA)
#define SM_MX (cb + K_SM_MX)
#define SM_UL (cb + K_SM_UL)
#define SM_AL (cb + K_SM_AL)
#define SM_FIN (cb + K_SM_FIN)
#define SM_OW (cb + K_SM_OW)
#define SM_FW (cb + K_SM_FW)
#define SM_ZERO (cb + K_SM_ZERO)
#define SM_EP (cb + K_SM_EP)
#define SM_FLAG (cb + K_SM_FLAG)
#define BAR_FULL (cb + K_BAR_FULL)
#define BAR_EMPTY (cb + K_BAR_EMPTY)
#define BAR_W (cb + K_BAR_W)
#define BAR_EP (cb + K_BAR_EP)
#define BAR_WT (cb + K_BAR_WT)
#define BAR_V (cb + K_BAR_V)
#define BAR_JOB (cb + K_BAR_JOB)
#define SM_INFO (cb + K_SM_INFO)
#define SM_TS (cb + K_SM_TS)
#define SM_WQ (cb + K_SM_WQ)
#define SM_WK (cb + K_SM_WK)
#define SM_Q (cb + K_SM_Q)
#define SM_RED (cb + K_SM_RED)
#define SM_WV (cb + K_SM_WV)
#define SM_WO (cb + K_SM_WO)

struct __align__(128) Scratch {
    unsigned epoch, ctr, pad[30];
    unsigned flagW[128];
    uint4 qk[12 * 32];
    uint32_t wvo[3 * 4 * 12 * 128];
    uint4 M[8 * 128 * 2];
    uint4 L[8 * 128 * 2];
    uint4 T[8 * 128 * 2];
    uint4 A[8 * 64];
};
__device__ Scratch g_s;

__device__ __forceinline__ void spin_guard(unsigned it) {
    asm volatile("{\n.reg .pred p;\n.reg .b64 z;\nsetp.gt.u32 p, %0, %1;\nmov.b64 z, 0;\n@p st.global.u32 [z], %0;\n}" ::"r"(it), "n"(SPIN_LIMIT));
}
__device__ __forceinline__ uint32_t smem_u32(const void* p) { return (uint32_t)__cvta_generic_to_shared(p); }
__device__ __forceinline__ void mbar_init(uint32_t bar, int cnt) { asm volatile("mbarrier.init.shared::cta.b64 [%0], %1;" ::"r"(bar), "r"(cnt) : "memory"); }
__device__ __forceinline__ void mbar_expect_tx(uint32_t bar, uint32_t bytes) { asm volatile("mbarrier.arrive.expect_tx.shared::cta.b64 _, [%0], %1;" ::"r"(bar), "r"(bytes) : "memory"); }
__device__ __forceinline__ void mbar_arrive_if(uint32_t bar, uint32_t cond) {
    asm volatile("{\n.reg .pred p;\nsetp.ne.u32 p, %1, 0;\n@p mbarrier.arrive.shared::cta.b64 _, [%0];\n}" ::"r"(bar), "r"(cond) : "memory");
}
__device__ __forceinline__ void mbar_wait(uint32_t bar, uint32_t parity) {
    asm volatile("{\n.reg .pred p;\n.reg .u32 c;\n.reg .b64 z;\nmov.u32 c, 0;\nmov.b64 z, 0;\nbra.uni T_%=;\n"
                 "W_%=:\nadd.u32 c, c, 1;\nsetp.gt.u32 p, c, %2;\n@p st.global.u32 [z], c;\n"
                 "T_%=:\nmbarrier.try_wait.parity.shared::cta.b64 p, [%0], %1;\n@!p bra W_%=;\n}"
                 ::"r"(bar), "r"(parity), "n"(SPIN_LIMIT / 4) : "memory");
}
__device__ __forceinline__ void mbar_wait_u(uint32_t bar, uint32_t parity) {
    asm volatile("{\n.reg .pred p;\n.reg .u32 c;\n.reg .b64 z;\nmov.u32 c, 0;\nmov.b64 z, 0;\nbra.uni T_%=;\n"
                 "W_%=:\nadd.u32 c, c, 1;\nsetp.gt.u32 p, c, %2;\n@p st.global.u32 [z], c;\n"
                 "T_%=:\nmbarrier.try_wait.parity.shared::cta.b64 p, [%0], %1;\n@!p bra.uni W_%=;\n}"
                 ::"r"(bar), "r"(parity), "n"(SPIN_LIMIT / 4) : "memory");
}
__device__ __forceinline__ bool mbar_test(uint32_t bar, uint32_t parity) {
    uint32_t ok;
    asm volatile("{\n.reg .pred p;\nmbarrier.test_wait.parity.shared::cta.b64 p, [%1], %2;\nselp.u32 %0, 1, 0, p;\n}" : "=r"(ok) : "r"(bar), "r"(parity) : "memory");
    return ok != 0;
}
__device__ __forceinline__ void tma3d(uint32_t dst, const CUtensorMap* tm, int c0, int c1, int c2, uint32_t bar) {
    asm volatile("cp.async.bulk.tensor.3d.shared::cluster.global.mbarrier::complete_tx::bytes.L2::cache_hint [%0], [%1, {%3, %4, %5}], [%2], %6;"
                 ::"r"(dst), "l"(tm), "r"(bar), "r"(c0), "r"(c1), "r"(c2), "l"(EVICT_FIRST) : "memory");
}
__device__ __forceinline__ void tma2d(uint32_t dst, const CUtensorMap* tm, int c0, int c1, uint32_t bar) {
    asm volatile("cp.async.bulk.tensor.2d.shared::cluster.global.mbarrier::complete_tx::bytes.L2::cache_hint [%0], [%1, {%3, %4}], [%2], %5;"
                 ::"r"(dst), "l"(tm), "r"(bar), "r"(c0), "r"(c1), "l"(EVICT_FIRST) : "memory");
}
__device__ __forceinline__ void tma2dn(uint32_t dst, const CUtensorMap* tm, int c0, int c1, uint32_t bar) {
    asm volatile("cp.async.bulk.tensor.2d.shared::cluster.global.mbarrier::complete_tx::bytes [%0], [%1, {%3, %4}], [%2];"
                 ::"r"(dst), "l"(tm), "r"(bar), "r"(c0), "r"(c1) : "memory");
}
__device__ __forceinline__ void bulk_g2s(uint32_t dst, const void* src, uint32_t bytes, uint32_t bar) {
    asm volatile("cp.async.bulk.shared::cluster.global.mbarrier::complete_tx::bytes [%0], [%1], %2, [%3];" ::"r"(dst), "l"(src), "r"(bytes), "r"(bar) : "memory");
}
__device__ __forceinline__ void ldsm4(uint32_t a, uint32_t (&r)[4]) {
    asm volatile("ldmatrix.sync.aligned.m8n8.x4.shared.b16 {%0,%1,%2,%3}, [%4];" : "=r"(r[0]), "=r"(r[1]), "=r"(r[2]), "=r"(r[3]) : "r"(a) : "memory");
}
__device__ __forceinline__ void ldsm4t(uint32_t a, uint32_t (&r)[4]) {
    asm volatile("ldmatrix.sync.aligned.m8n8.x4.trans.shared.b16 {%0,%1,%2,%3}, [%4];" : "=r"(r[0]), "=r"(r[1]), "=r"(r[2]), "=r"(r[3]) : "r"(a) : "memory");
}
__device__ __forceinline__ void stsm4(uint32_t a, uint32_t x, uint32_t y, uint32_t z, uint32_t w) {
    asm volatile("stmatrix.sync.aligned.m8n8.x4.shared.b16 [%0], {%1,%2,%3,%4};" ::"r"(a), "r"(x), "r"(y), "r"(z), "r"(w) : "memory");
}
__device__ __forceinline__ void mma16816(float (&d)[4], uint32_t a0, uint32_t a1, uint32_t a2, uint32_t a3, uint32_t b0, uint32_t b1) {
    asm volatile("mma.sync.aligned.m16n8k16.row.col.f32.bf16.bf16.f32 {%0,%1,%2,%3}, {%4,%5,%6,%7}, {%8,%9}, {%0,%1,%2,%3};"
        : "+f"(d[0]), "+f"(d[1]), "+f"(d[2]), "+f"(d[3]) : "r"(a0), "r"(a1), "r"(a2), "r"(a3), "r"(b0), "r"(b1));
}
__device__ __forceinline__ void mma_sp(float (&d)[4], const uint32_t (&a)[4], const uint32_t (&b)[4], uint32_t meta = 0xEEEE4444u) {
    asm volatile("mma.sp::ordered_metadata.sync.aligned.m16n8k32.row.col.f32.bf16.bf16.f32 {%0,%1,%2,%3}, {%4,%5,%6,%7}, {%8,%9,%10,%11}, {%12,%12,%12,%12}, %13, 0x0;"
        : "=f"(d[0]), "=f"(d[1]), "=f"(d[2]), "=f"(d[3])
        : "r"(a[0]), "r"(a[1]), "r"(a[2]), "r"(a[3]), "r"(b[0]), "r"(b[1]), "r"(b[2]), "r"(b[3]), "f"(0.f), "r"(meta));
}
__device__ __forceinline__ uint32_t badd2v(uint32_t a, uint32_t b) { uint32_t d; asm volatile("add.rn.bf16x2 %0, %1, %2;" : "=r"(d) : "r"(a), "r"(b)); return d; }
__device__ __forceinline__ uint32_t negv(uint32_t a) { uint32_t d; asm volatile("xor.b32 %0, %1, 0x80008000;" : "=r"(d) : "r"(a)); return d; }
__device__ __forceinline__ uint32_t pack2(float lo, float hi) { uint32_t d; asm("cvt.rn.bf16x2.f32 %0, %1, %2;" : "=r"(d) : "f"(hi), "f"(lo)); return d; }
__device__ __forceinline__ float bf_lo(uint32_t v) { return __uint_as_float(v << 16); }
__device__ __forceinline__ float bf_hi(uint32_t v) { return __uint_as_float(v & 0xffff0000u); }
__device__ __forceinline__ float ex2(float x) { float y; asm("ex2.approx.ftz.f32 %0, %1;" : "=f"(y) : "f"(x)); return y; }
__device__ __forceinline__ float rsq(float x) { float y; asm("rsqrt.approx.ftz.f32 %0, %1;" : "=f"(y) : "f"(x)); return y; }
__device__ __forceinline__ void bar_sync(int id, int n) { asm volatile("bar.sync %0, %1;" ::"r"(id), "r"(n) : "memory"); }
__device__ __forceinline__ void bar_arrive(int id, int n) { asm volatile("bar.arrive %0, %1;" ::"r"(id), "r"(n) : "memory"); }
__device__ __forceinline__ unsigned ld_acquire(const unsigned* p) { unsigned v; asm volatile("ld.acquire.gpu.global.u32 %0, [%1];" : "=r"(v) : "l"(p) : "memory"); return v; }
__device__ __forceinline__ void st_release(unsigned* p, unsigned v) { asm volatile("st.release.gpu.global.u32 [%0], %1;" ::"l"(p), "r"(v) : "memory"); }
__device__ __forceinline__ uint4 ld_relaxed4(const uint4* p) {
    uint4 v; asm volatile("ld.relaxed.gpu.global.v4.u32 {%0,%1,%2,%3}, [%4];" : "=r"(v.x), "=r"(v.y), "=r"(v.z), "=r"(v.w) : "l"(p) : "memory"); return v;
}
__device__ __forceinline__ void ld_relaxed4_if(uint4& v, const uint4* p, uint32_t cond) {
    asm volatile("{\n.reg .pred p;\nsetp.ne.u32 p, %5, 0;\n@p ld.relaxed.gpu.global.v4.u32 {%0,%1,%2,%3}, [%4];\n}"
                 : "+r"(v.x), "+r"(v.y), "+r"(v.z), "+r"(v.w) : "l"(p), "r"(cond) : "memory");
}
__device__ __forceinline__ uint32_t collect(const uint4* tp, uint32_t par, uint32_t on) {
    uint32_t t;
    asm volatile("{\n.reg .pred p, q, r;\n.reg .b32 u, c;\n.reg .b64 z;\nmov.b32 c, 0;\nmov.b64 z, 0;\nmov.b32 %0, 0;\nsetp.ne.u32 r, %3, 0;\n"
                 "L_%=:\n@r ld.relaxed.gpu.global.u32 %0, [%1];\nadd.u32 c, c, 1;\nsetp.gt.u32 q, c, %4;\n@q st.global.u32 [z], c;\n"
                 "lop3.b32 u, %0, %2, %3, 0x28;\nsetp.ne.u32 p, u, 0;\nvote.sync.any.pred p, p, -1;\n@p bra.uni L_%=;\n}"
                 : "=&r"(t) : "l"(tp), "r"(par), "r"(on), "n"(SPIN_LIMIT) : "memory");
    return t;
}
__device__ __forceinline__ void load_at(float2& v, uint32_t on, uint32_t tl, const float2* p, uint32_t id) {
    asm volatile("{\n.reg .pred q, r;\n.reg .b32 t0, t1;\n.reg .b64 g;\n"
                 "A_%=:\nmov.u64 g, %%globaltimer;\ncvt.u32.u64 t0, g;\nsub.u32 t0, t0, %3;\nsetp.lt.s32 q, t0, 0;\n@q bra.uni A_%=;\n"
                 "prmt.b32 t1, %2, t0, %5;\n"
                 "prmt.b32 t1, t1, t1, %5;\n"
                 "prmt.b32 t1, t1, t1, %5;\n"
                 "setp.ne.u32 r, t1, 0;\n@r ld.relaxed.gpu.global.v2.f32 {%0,%1}, [%4];\n}"
                 : "+f"(v.x), "+f"(v.y) : "r"(on), "r"(tl), "l"(p), "r"(id) : "memory");
}
__device__ __forceinline__ void st_async_if(uint32_t dst, uint32_t a, uint32_t b, uint32_t c, uint32_t d, uint32_t bar, uint32_t cond) {
    asm volatile("{\n.reg .pred p;\nsetp.ne.u32 p, %6, 0;\n@p st.async.weak.shared::cluster.mbarrier::complete_tx::bytes.v4.b32 [%0], {%1,%2,%3,%4}, [%5];\n}"
                 ::"r"(dst), "r"(a), "r"(b), "r"(c), "r"(d), "r"(bar), "r"(cond) : "memory");
}
__device__ __forceinline__ void red_if(__nv_bfloat16* p, uint32_t a, uint32_t b, uint32_t c, uint32_t d, bool cond) {
    asm volatile("{\n.reg .pred p;\nsetp.ne.u32 p, %5, 0;\n@p red.global.add.noftz.v4.bf16x2 [%0], {%1,%2,%3,%4};\n}"
                 ::"l"(p), "r"(a), "r"(b), "r"(c), "r"(d), "r"((uint32_t)cond) : "memory");
}
__device__ __forceinline__ uint32_t mapa(uint32_t a, uint32_t rank) { uint32_t d; asm volatile("mapa.shared::cluster.u32 %0, %1, %2;" : "=r"(d) : "r"(a), "r"(rank)); return d; }
__device__ __forceinline__ uint32_t f2uv(float x) { uint32_t r; asm volatile("cvt.rzi.u32.f32 %0, %1;" : "=r"(r) : "f"(x)); return r; }
__device__ __forceinline__ void sts16(uint32_t a, uint32_t x) { asm volatile("{\n.reg .b16 h;\ncvt.u16.u32 h, %1;\nst.shared.u16 [%0], h;\n}" ::"r"(a), "r"(x) : "memory"); }
__device__ __forceinline__ void st_v4(uint4* p, uint32_t a, uint32_t b, uint32_t c, uint32_t d) {
    asm volatile("st.relaxed.gpu.global.v4.u32 [%0], {%1,%2,%3,%4};" ::"l"(p), "r"(a), "r"(b), "r"(c), "r"(d) : "memory");
}
__device__ __forceinline__ void st_v4_if(uint4* p, uint32_t a, uint32_t b, uint32_t c, uint32_t d, bool cond) {
    asm volatile("{\n.reg .pred p;\nsetp.ne.u32 p, %5, 0;\n@p st.relaxed.gpu.global.v4.u32 [%0], {%1,%2,%3,%4};\n}"
                 ::"l"(p), "r"(a), "r"(b), "r"(c), "r"(d), "r"((uint32_t)cond) : "memory");
}
__device__ __forceinline__ uint32_t pack2t(float lo, float hi, uint32_t par) {
    return (__byte_perm(__float_as_uint(lo) + ((par ^ 1u) << 16), pack2(0.f, hi), 0x7632) & ~1u) | par;
}
__device__ __forceinline__ void lds128(uint32_t a, uint32_t (&r)[4]) {
    asm volatile("ld.shared.v4.u32 {%0,%1,%2,%3}, [%4];" : "=r"(r[0]), "=r"(r[1]), "=r"(r[2]), "=r"(r[3]) : "r"(a) : "memory");
}
__device__ __forceinline__ float sum4(const uint32_t (&r)[4]) {
    return (__uint_as_float(r[0]) + __uint_as_float(r[1])) + (__uint_as_float(r[2]) + __uint_as_float(r[3]));
}
__device__ __forceinline__ void sts32(uint32_t a, uint32_t x) { asm volatile("st.shared.u32 [%0], %1;" ::"r"(a), "r"(x) : "memory"); }
__device__ __forceinline__ void stsf(uint32_t a, float x) { asm volatile("st.shared.f32 [%0], %1;" ::"r"(a), "f"(x) : "memory"); }
__device__ __forceinline__ void stsf2(uint32_t a, float x, float y) { asm volatile("st.shared.v2.f32 [%0], {%1,%2};" ::"r"(a), "f"(x), "f"(y) : "memory"); }
__device__ __forceinline__ float ldsf(uint32_t a) { float v; asm volatile("ld.shared.f32 %0, [%1];" : "=f"(v) : "r"(a) : "memory"); return v; }
__device__ __forceinline__ float2 ldsf2(uint32_t a) { float2 v; asm volatile("ld.shared.v2.f32 {%0,%1}, [%2];" : "=f"(v.x), "=f"(v.y) : "r"(a) : "memory"); return v; }
__device__ __forceinline__ uint32_t lds32(uint32_t a) { uint32_t v; asm volatile("ld.shared.u32 %0, [%1];" : "=r"(v) : "r"(a) : "memory"); return v; }
__device__ __forceinline__ uint32_t ldsv32(uint32_t a) { uint32_t v; asm volatile("ld.volatile.shared.u32 %0, [%1];" : "=r"(v) : "r"(a) : "memory"); return v; }
__device__ __forceinline__ float warp_max(float x) {
    int k = __float_as_int(x);
    k = __reduce_max_sync(0xffffffffu, k ^ ((k >> 31) & 0x7fffffff));
    return __int_as_float(k ^ ((k >> 31) & 0x7fffffff));
}
__device__ __forceinline__ uint32_t now_ns() { uint32_t t; asm volatile("mov.u32 %0, %globaltimer_lo;" : "=r"(t) :: "memory"); return t; }
__device__ __forceinline__ uint32_t clk32() { uint32_t t; asm volatile("mov.u32 %0, %clock;" : "=r"(t) :: "memory"); return t; }
__device__ __forceinline__ void sched_fence(uint32_t& sink) { uint64_t t; asm volatile("mov.u64 %0, %clock64;" : "=l"(t) :: "memory"); sink ^= (uint32_t)(t >> 32); }
__device__ __forceinline__ void sink_if(uint32_t addr, uint32_t sink, uint32_t cond) {
    asm volatile("{\n.reg .pred p;\nsetp.ne.u32 p, %2, 0;\n@p st.shared.u32 [%0], %1;\n}" ::"r"(addr), "r"(sink), "r"(cond) : "memory");
}
__device__ __forceinline__ uint32_t opaque(uint32_t v, int lane) { return __shfl_sync(0xffffffffu, v, lane); }

__device__ __forceinline__ void el_arrive(uint32_t bar) {
    asm volatile("{\n.reg .pred p;\nelect.sync _|p, -1;\n@p mbarrier.arrive.shared::cta.b64 _, [%0];\n}" ::"r"(bar) : "memory");
}
__device__ __forceinline__ void el_expect_tx(uint32_t bar, uint32_t bytes) {
    asm volatile("{\n.reg .pred p;\nelect.sync _|p, -1;\n@p mbarrier.arrive.expect_tx.shared::cta.b64 _, [%0], %1;\n}" ::"r"(bar), "r"(bytes) : "memory");
}
__device__ __forceinline__ void el_tile(uint32_t cb, int s, int t, const CUtensorMap* tm0, const CUtensorMap* tm1) {
    asm volatile("{\n.reg .pred p;\nelect.sync _|p, -1;\n"
                 "@p cp.async.bulk.tensor.3d.shared::cluster.global.mbarrier::complete_tx::bytes.L2::cache_hint [%0], [%1, {%9, %4, %5}], [%3], %7;\n"
                 "@p cp.async.bulk.tensor.2d.shared::cluster.global.mbarrier::complete_tx::bytes.L2::cache_hint [%8], [%2, {%9, %6}], [%3], %7;\n}"
                 ::"r"(SB + s * STAGE_BYTES), "l"(tm0), "l"(tm1), "r"(BAR_FULL + 8 * s), "r"((t & 15) * 96), "r"((t >> 4) * 2), "r"(t * 48),
                   "l"(EVICT_FIRST), "r"(SB + s * STAGE_BYTES + 24576), "r"(0) : "memory");
}
__device__ __forceinline__ void el_bulk(uint32_t dst, const void* src, uint32_t bytes, uint32_t bar) {
    asm volatile("{\n.reg .pred p;\nelect.sync _|p, -1;\n"
                 "@p cp.async.bulk.shared::cluster.global.mbarrier::complete_tx::bytes [%0], [%1], %2, [%3];\n}" ::"r"(dst), "l"(src), "r"(bytes), "r"(bar) : "memory");
}
__device__ __forceinline__ void issue_tile(uint32_t cb, int s, int t, const CUtensorMap* tm0, const CUtensorMap* tm1) {
    const uint32_t bar = BAR_FULL + 8 * s;
    mbar_expect_tx(bar, STAGE_BYTES);
    tma3d(SB + s * STAGE_BYTES, tm0, 0, (t & 15) * 96, (t >> 4) * 2, bar);
    tma2d(SB + s * STAGE_BYTES + 24576, tm1, 0, t * 48, bar);
}

__global__ void __cluster_dims__(CL, 1, 1) __launch_bounds__(384, 1)
fused_kernel(uint64_t scn  , const __nv_bfloat16* __restrict__ q,
             const char* f0, const char* f1, const char* wq, const char* wk,
             const __grid_constant__ CUtensorMap tm0, const __grid_constant__ CUtensorMap tm1,
             const __grid_constant__ CUtensorMap tmq, const __grid_constant__ CUtensorMap tmk,
             const __grid_constant__ CUtensorMap tmv, const __grid_constant__ CUtensorMap tmo,
             __nv_bfloat16* __restrict__ out, const uint4* scl) {
    extern __shared__ __align__(1024) char smem_raw[];
    const int tid = threadIdx.x, warp = tid >> 5, lane = tid & 31;
    const int bid = blockIdx.x, e0 = bid - NSERV;
    const uint32_t cb0 = smem_u32(smem_raw) - K_SB;

    Scratch* const sc = reinterpret_cast<Scratch*>(scn & ~(uint64_t)127);
    [[maybe_unused]] const uint32_t cb = cb0;
    const int NS = ((int)scn & 127) + 1;
    const int NE = NS - NSERV, src = bid;
    int ticket = 0;
    asm volatile("{\n.reg .pred p, s;\n.reg .b32 a, b;\n.reg .b64 x, y;\nsetp.ne.u32 p, %8, 256;\nsetp.lt.s32 s, %9, 0;\n@p bra N_%=;\n@s bra.uni V_%=;\n"
                 "and.b32 a, %9, -16;\nadd.u32 a, a, %9;\nmad.wide.u32 x, a, 12288, %1;\nmad.wide.u32 y, %9, 6144, %2;\n"
                 "cp.async.bulk.prefetch.L2.global.L2::cache_hint [x], 12288, %6;\ncp.async.bulk.prefetch.L2.global.L2::cache_hint [y], 6144, %6;\n"
                 "cp.async.bulk.prefetch.L2.global.L2::cache_hint [x+196608], 12288, %6;\n"
                 "bra E_%=;\n"
                 "V_%=:\nadd.u32 b, %9, %10;\nmad.wide.u32 x, b, 512, %5;\ncp.async.bulk.prefetch.L2.global [x], 512;\n"
                 "mad.wide.u32 x, b, 6144, %4;\ncp.async.bulk.prefetch.L2.global [x], 6144;\n"
                 "mad.wide.u32 y, b, 6144, %3;\ncp.async.bulk.prefetch.L2.global [y], 6144;\nbra E_%=;\n"
                 "N_%=:\nsetp.eq.u32 p, %8, 288;\n@p ld.relaxed.gpu.global.u32 %0, [%7];\nE_%=:\n}"
                 : "+r"(ticket) : "l"(f0), "l"(f1), "l"(wq), "l"(wk), "l"(q), "l"(EVICT_FIRST), "l"(&sc->epoch), "r"(tid), "r"(e0), "n"(NSERV) : "memory");
    if (tid == 320) {
        mbar_init(BAR_FULL, 2);
        if (e0 >= 0) {
            issue_tile(cb, 0, e0, &tm0, &tm1);
        } else {
#pragma unroll
            for (int i = 0; i < 5; ++i) mbar_init(BAR_JOB + 8 * i, 1);
            mbar_expect_tx(BAR_JOB, 32 * CH * 2);
            bulk_g2s(SM_Q, q, 16 * CH * 2, BAR_JOB);
            tma2dn(SM_WK, &tmk, 0, bid * 48, BAR_JOB);
#pragma unroll
            for (int c = 0; c < 3; ++c) {
                mbar_expect_tx(BAR_JOB + 8 + 8 * c, 64 * CH * 2);
                tma2dn(SM_WQ + c * 64 * CH * 2, &tmq, 0, c * 192, BAR_JOB + 8 + 8 * c);
            }
        }
    } else if (tid == 0) {
#pragma unroll
        for (int i = 1; i < 2 * STAGES + 6; ++i)
            mbar_init(BAR_FULL + 8 * i, i < STAGES ? 2 : 1);
#pragma unroll
        for (int e = 0; e < 3; ++e) mbar_expect_tx(BAR_V + 8 * e, CL * 256);
        asm volatile("fence.mbarrier_init.release.cluster;" ::: "memory");
    } else if (warp == 1) {
        stsf2(SM_ZERO + lane * 8, 0.f, 0.f);
        if (lane < 4) stsf2(SM_EP + lane * 8, 0.f, 0.f);
        if (lane <= STAGES) sts32(SM_INFO + 4 * lane, lane == STAGES - 1);
        spin_guard((smem_u32(smem_raw) & 0xffffffu) == K_SB ? 0u : ~0u);
    }
    __syncthreads();
    if (warp != 11) asm volatile("barrier.cluster.arrive.relaxed.aligned;" ::: "memory");

    const int g = lane >> 2, j = lane & 3, m4 = lane >> 3, r8 = lane & 7;

    if (e0 < 0) {
        if (tid == 320) {
            mbar_expect_tx(BAR_JOB + 32, (CH + 16) * CH * 2);
            tma2dn(SM_WO, &tmo, bid * 16, 0, BAR_JOB + 32);
#pragma unroll
            for (int c = 0; c < 3; ++c) tma2dn(SM_WV + c * 64 * CH * 2, &tmv, 0, c * 192, BAR_JOB + 32);
        }
        if (tid == 288) sts32(SM_EP, ticket + 1);
        if (warp == 9) st_v4(&sc->qk[bid * 32 + lane], __shfl_sync(0xffffffffu, ticket, 0), 0u, 0u, 0u);
        st_v4_if(reinterpret_cast<uint4*>(sc->flagW) + bid * 2 + (tid & 1), 0u, 0u, 0u, 0u, tid < 2);
        __syncwarp();
        mbar_wait(BAR_JOB, 0);
        if (warp == 10) {
            uint32_t t[4];
            lds128(SM_Q + bid * 512 + lane * 16, t);
            st_v4(reinterpret_cast<uint4*>(out) + bid * 32 + lane, t[0], t[1], t[2], t[3]);
            st_v4_if(&sc->A[(bid & 7) * 64 + (lane & 7)], 0u, 0u, 0u, 0u, bid < 8 && lane < 8);
        }
        if (warp < 8) {
            const int row = 2 * warp + (lane >> 4), c0 = (lane & 15) * 8;
            float v[3][4];
#pragma unroll
            for (int c = 0; c < 3; ++c) {
                const float2 t = ldsf2(SM_Q + row * 384 + c * 128 + c0);
                v[c][0] = bf_lo(__float_as_uint(t.x)); v[c][1] = bf_hi(__float_as_uint(t.x));
                v[c][2] = bf_lo(__float_as_uint(t.y)); v[c][3] = bf_hi(__float_as_uint(t.y));
            }
            float sum = ((v[0][0] + v[0][1]) + (v[0][2] + v[0][3])) + ((v[1][0] + v[1][1]) + (v[1][2] + v[1][3])) + ((v[2][0] + v[2][1]) + (v[2][2] + v[2][3]));
#pragma unroll
            for (int d = 1; d < 16; d <<= 1) sum += __shfl_xor_sync(0xffffffffu, sum, d);
            const float mean = sum * (1.f / CH);
            float ss[3];
#pragma unroll
            for (int c = 0; c < 3; ++c) {
#pragma unroll
                for (int e = 0; e < 4; ++e) v[c][e] -= mean;
                ss[c] = fmaf(v[c][0], v[c][0], v[c][1] * v[c][1]) + fmaf(v[c][2], v[c][2], v[c][3] * v[c][3]);
            }
            sum = ss[0] + ss[1] + ss[2];
#pragma unroll
            for (int d = 1; d < 16; d <<= 1) sum += __shfl_xor_sync(0xffffffffu, sum, d);
            const float rstd = rsq(sum * (1.f / CH) + LN_EPS);
#pragma unroll
            for (int c = 0; c < 3; ++c)
                stsf2(SM_A + row * 400 + c * 128 + c0, __uint_as_float(pack2(v[c][0] * rstd, v[c][1] * rstd)), __uint_as_float(pack2(v[c][2] * rstd, v[c][3] * rstd)));
        }
        {
            float d[2][2][4];
#pragma unroll
            for (int c = 0; c < 4; ++c) d[0][0][c] = d[0][1][c] = d[1][0][c] = d[1][1][c] = 0.f;
            uint32_t a[12][4], qa[4];
#pragma unroll
            for (int k = 0; k < 12; ++k) {
                const int r = 3 * ((m4 & 1) * 8 + r8) + (k >> 2);
                ldsm4(SM_WK + r * 128 + ((((k & 3) * 2 + (m4 >> 1)) ^ (r & 7)) << 4), a[k]);
            }
            mbar_wait(BAR_JOB + 8 + 8 * (warp >> 2), 0);
#pragma unroll
            for (int k = 0; k < 12; ++k) {
                uint32_t b[4];
                const int r = 3 * ((m4 >> 1) * 8 + r8) + (k >> 2);
                ldsm4(SM_WQ + warp * 6144 + r * 128 + ((((k & 3) * 2 + (m4 & 1)) ^ (r & 7)) << 4), b);
                mma16816(d[0][k & 1], a[k][0], a[k][1], a[k][2], a[k][3], b[0], b[1]);
                mma16816(d[1][k & 1], a[k][0], a[k][1], a[k][2], a[k][3], b[2], b[3]);
            }
            bar_sync(1, 384);
            ldsm4(SM_A + ((m4 & 1) * 8 + r8) * 400 + (16 * warp + (m4 >> 1) * 8) * 2, qa);
#pragma unroll
            for (int nb = 0; nb < 2; ++nb) {
                uint32_t hi[2], lo[2];
#pragma unroll
                for (int t = 0; t < 2; ++t) {
                    const float v0 = d[t][0][2 * nb] + d[t][1][2 * nb], v1 = d[t][0][2 * nb + 1] + d[t][1][2 * nb + 1];
                    hi[t] = pack2(v0, v1);
                    lo[t] = pack2(v0 - bf_lo(hi[t]), v1 - bf_hi(hi[t]));
                }
                float e[4] = {0.f, 0.f, 0.f, 0.f};
                mma16816(e, qa[0], qa[1], qa[2], qa[3], hi[0], hi[1]);
                mma16816(e, qa[0], qa[1], qa[2], qa[3], lo[0], lo[1]);
                stsm4(SM_RED + (warp * 2 + nb) * 512 + lane * 16, __float_as_uint(e[0]), __float_as_uint(e[1]), __float_as_uint(e[2]), __float_as_uint(e[3]));
            }
            bar_sync(1, 384);
            if (warp == 0) {
                float r[8] = {0.f, 0.f, 0.f, 0.f, 0.f, 0.f, 0.f, 0.f};
#pragma unroll
                for (int u = 0; u < 24; ++u) {
                    uint32_t e[4];
                    ldsm4(SM_RED + u * 512 + lane * 16, e);
#pragma unroll
                    for (int c = 0; c < 4; ++c) r[(u & 1) * 4 + c] += __uint_as_float(e[c]);
                }
                const float qs = 1.4426950408889634f * 13.856406460551018f;
                const uint32_t a0 = pack2t(r[0] * qs, r[1] * qs, lds32(SM_EP) & 1u), a1 = pack2(r[2] * qs, r[3] * qs);
                const uint32_t a2 = pack2(r[4] * qs, r[5] * qs), a3 = pack2(r[6] * qs, r[7] * qs);
                st_v4(&sc->qk[bid * 32 + lane], a0, a1, a2, a3);
            }
        }
        {
            mbar_wait(BAR_JOB + 32, 0);
            float d[2][4] = {{0.f, 0.f, 0.f, 0.f}, {0.f, 0.f, 0.f, 0.f}};
#pragma unroll 1
            for (int k = 0; k < 12; ++k) {
                uint32_t a[4], b[4];
                ldsm4t(SM_WO + (16 * k + (m4 >> 1) * 8 + r8) * 32 + (m4 & 1) * 16, a);
                const int r = 3 * ((m4 >> 1) * 8 + r8) + (k >> 2);
                ldsm4(SM_WV + warp * 6144 + r * 128 + ((((k & 3) * 2 + (m4 & 1)) ^ (r & 7)) << 4), b);
                mma16816(d[0], a[0], a[1], a[2], a[3], b[0], b[1]);
                mma16816(d[1], a[0], a[1], a[2], a[3], b[2], b[3]);
            }
            float s0 = (d[0][0] + d[0][1]) + (d[1][0] + d[1][1]), s1 = (d[0][2] + d[0][3]) + (d[1][2] + d[1][3]);
            s0 += __shfl_xor_sync(0xffffffffu, s0, 1); s1 += __shfl_xor_sync(0xffffffffu, s1, 1);
            s0 += __shfl_xor_sync(0xffffffffu, s0, 2); s1 += __shfl_xor_sync(0xffffffffu, s1, 2);
            if (j == 0) stsf2(SM_FW + (warp * 8 + g) * 8, s0, s1);
            bar_sync(1, 384);
            s0 = s1 = 0.f;
#pragma unroll 1
            for (int u = 0; u < 12; ++u) { const float2 t = ldsf2(SM_FW + (u * 8 + g) * 8); s0 += t.x; s1 += t.y; }
            s0 *= 1.f / CH; s1 *= 1.f / CH;
            const int h = bid / 3, i = (warp + 12 - 3 * h) % 12;
            uint32_t* wp = &sc->wvo[(((i >> 2) * 4 + h) * 12 + (i & 3) * 3 + bid % 3) * 128 + lane];
            wp[0] = pack2(d[0][0] - s0, d[0][1] - s0); wp[32] = pack2(d[1][0] - s0, d[1][1] - s0);
            wp[64] = pack2(d[0][2] - s1, d[0][3] - s1); wp[96] = pack2(d[1][2] - s1, d[1][3] - s1);
            asm volatile("fence.proxy.async;" ::: "memory");
            bar_sync(1, 384);
            if (tid == 0) st_release(&sc->flagW[bid * 8], lds32(SM_EP));
        }
    }

    if (warp < 4) {
        asm volatile("setmaxnreg.inc.sync.aligned.u32 176;");
        const uint32_t cb = opaque(cb0, lane);
        const int w = warp;
        uint32_t oa[6], ob[6];
#pragma unroll
        for (int b = 0; b < 3; ++b) {
            int r = 3 * (8 * w + r8) + b;
            uint32_t o = SB + r * 128 + ((m4 ^ (r & 7)) << 4);
            oa[2 * b] = opaque(o, lane); oa[2 * b + 1] = opaque(o ^ 64u, lane);
            r = 3 * (4 * w + (r8 >> 1)) + b;
            o = SB + 24576 + r * 128 + ((m4 ^ 1 ^ (r & 7)) << 4);
            ob[2 * b] = opaque(o, lane); ob[2 * b + 1] = opaque(o ^ 64u, lane);
        }
        uint32_t one[4][2];
#pragma unroll
        for (int i = 0; i < 4; ++i) {
            one[i][0] = 0x3F803F80u + lds32(SM_ZERO + (lane + 2 * i) * 4); one[i][1] = 0x3F803F80u + lds32(SM_ZERO + (lane + 2 * i + 1) * 4);
        }
        const uint32_t dmask = opaque(j == (g >> 1) ? 0xffff0000u : 0u, lane);
        const float dsel = __uint_as_float(opaque(j == (g >> 1) ? 0x3f800000u : 0u, lane));
        const bool odd = opaque(g & 1, lane) != 0;
        uint32_t first = 0;
        const uint32_t pst = opaque(SM_P + w * 512 + lane * 16, lane);
        const uint32_t lst = opaque(SM_UL + 256 + (j & 1) * 128 + g * 16 + w * 4, lane), loff = opaque(((g * 128 + src) * 2 + (j & 1)) * 16, lane);
        const bool odj = lst & 128;
        uint32_t qk[12][4];
#pragma unroll
        for (int k = 0; k < 12; ++k) qk[k][0] = qk[k][1] = qk[k][2] = qk[k][3] = 0u;
        float R0 = 0.f, R1 = 0.f;
        float m0 = -INFINITY, m1 = -INFINITY, l0 = 0.f, l1 = 0.f;
        int s = STAGES - 1; uint32_t st = (STAGES - 1) * STAGE_BYTES, ph = 1, pbuf = 0;
        uint32_t sink = lds32(SM_ZERO + (lane + 8) * 4), seq = 0;
        mbar_wait(BAR_EP, 0);
#pragma unroll 1
        while (true) {
            mbar_wait(BAR_FULL + 8 * s, ph);
            uint32_t r0[6][4], r1[6][4], f[6][4];
            float S2[2][2][4], T2[2][2][4];
#pragma unroll
            for (int b = 0; b < 2; ++b)
#pragma unroll
                for (int c = 0; c < 4; ++c) { S2[0][b][c] = S2[1][b][c] = 0.f; T2[0][b][c] = T2[1][b][c] = 0.f; }
            uint32_t d0[2][2], d1[2][2];
#pragma unroll
            for (int n = 0; n < 2; ++n) { ldsm4(st + ob[n], f[n]); ldsm4(st + oa[n], r0[n]); ldsm4(st + oa[n] + 12288, r1[n]); }
            sched_fence(sink);
#pragma unroll
            for (int k = -1; k < 12; ++k) {
                const int n = (k + 1) / 2 + 2;
                if (n < 6) {
                    if ((k + 1) & 1) ldsm4(st + oa[n] + 12288, r1[n]);
                    else { ldsm4(st + ob[n], f[n]); ldsm4(st + oa[n], r0[n]); }
                }
                if (k == ORDER_AT) bar_arrive(8, 256);
                if (k >= 0) {
                    const int i = k >> 1, h = k & 1;
                    mma16816(T2[h][0], d0[h][0], one[h][0], d0[h][1], one[h][1], r0[i][2 * h], r0[i][2 * h + 1]);
                    mma16816(T2[h][1], d1[h][0], one[2 + h][0], d1[h][1], one[2 + h][1], r1[i][2 * h], r1[i][2 * h + 1]);
                    mma16816(S2[h][0], qk[k][0], qk[k][1], qk[k][2], qk[k][3], r0[i][2 * h], r0[i][2 * h + 1]);
                    mma16816(S2[h][1], qk[k][0], qk[k][1], qk[k][2], qk[k][3], r1[i][2 * h], r1[i][2 * h + 1]);
                }
                if (k < 11) {
                    const int i = (k + 1) >> 1, h = (k + 1) & 1;
#pragma unroll
                    for (int c = 0; c < 2; ++c) {
                        r0[i][2 * h + c] = badd2v(r0[i][2 * h + c], f[i][2 * h + (c ^ 1)]); r1[i][2 * h + c] = badd2v(r1[i][2 * h + c], f[i][2 * h + (c ^ 1)]);
                        d0[h][c] = negv(r0[i][2 * h + c]); d1[h][c] = negv(r1[i][2 * h + c]);
                    }
                    sched_fence(sink);
                }
            }
            float S[2][4], T[2][4];
#pragma unroll
            for (int b = 0; b < 2; ++b)
#pragma unroll
                for (int c = 0; c < 4; ++c) { S[b][c] = S2[0][b][c] + S2[1][b][c]; T[b][c] = T2[0][b][c] + T2[1][b][c]; }
            uint32_t rb[2];
#pragma unroll
            for (int b = 0; b < 2; ++b) {
                const float qd = odd ? T[b][1] : T[b][0], sd = odd ? T[b][3] : T[b][2];
                const float rd = rsq(fmaxf(fmaf(qd, -(float)CH, fmaf(-sd, sd, EPS2)), EPS2));
                const float hi = __uint_as_float(__float_as_uint(rd) & dmask);
                rb[b] = pack2(fmaf(rd, dsel, -hi), hi);
            }
            float rs[4] = {0.f, 0.f, 0.f, 0.f};
            mma16816(rs, 0x3F803F80u, 0u, 0u, 0x3F803F80u, rb[0], rb[1]);
            float y[2][4], z[2][4], p[2][4];
            uint32_t pp[4];
#pragma unroll
            for (int b = 0; b < 2; ++b) {
                y[b][0] = fmaf(-T[b][2], R0, S[b][0]); y[b][1] = fmaf(-T[b][3], R0, S[b][1]);
                y[b][2] = fmaf(-T[b][2], R1, S[b][2]); y[b][3] = fmaf(-T[b][3], R1, S[b][3]);
            }
            auto softmax_p = [&](uint32_t pb) {
#pragma unroll
                for (int b = 0; b < 2; ++b) {
                    z[b][0] = fmaf(rs[2 * b], y[b][0], -m0); z[b][1] = fmaf(rs[2 * b + 1], y[b][1], -m0);
                    z[b][2] = fmaf(rs[2 * b], y[b][2], -m1); z[b][3] = fmaf(rs[2 * b + 1], y[b][3], -m1);
#pragma unroll
                    for (int c = 0; c < 4; ++c) p[b][c] = ex2(z[b][c]);
                    pp[2 * b] = pack2(p[b][0] * rs[2 * b], p[b][1] * rs[2 * b + 1]);
                    pp[2 * b + 1] = pack2(p[b][2] * rs[2 * b], p[b][3] * rs[2 * b + 1]);
                }
                stsm4(pst + pb, pp[0], pp[1], pp[2], pp[3]);
            };
            softmax_p(pbuf);
            const float zmax = fmaxf(fmaxf(fmaxf(z[0][0], z[0][1]), fmaxf(z[0][2], z[0][3])), fmaxf(fmaxf(z[1][0], z[1][1]), fmaxf(z[1][2], z[1][3])));
            ++seq;
            sink_if(SM_FLAG + (pbuf >> 9), seq, zmax > RESCALE_TH);
            const uint32_t info = lds32(SM_INFO + 4 * s);
            bar_sync(1, 256);
            const float k0 = l0, k1 = l1;
            l0 += (p[0][0] + p[0][1]) + (p[1][0] + p[1][1]);
            l1 += (p[0][2] + p[0][3]) + (p[1][2] + p[1][3]);
            const uint32_t flag = lds32(SM_FLAG + (pbuf >> 9));
            mbar_arrive_if(BAR_EMPTY + 8 * s, first);
            pbuf ^= 2048;
            st += STAGE_BYTES;
            if (++s == STAGES) { s = 0; st = 0; ph ^= 1; }
            auto hand_over = [&](uint32_t fl) {
                const float e = (odj ? l1 : l0) + __shfl_xor_sync(0xffffffffu, odj ? l0 : l1, 1);
                const uint32_t ow = ldsv32(SM_OW + (loff >> 12) * 4);
                const float2 pub = ldsf2(SM_OW + 32 + (loff >> 12) * 8);
                const float e2 = __shfl_xor_sync(0xffffffffu, e, 2);
                float cnt = m0 == pub.x && m1 == pub.y && ow != ~0u ? 1.f : 2049.f, wt = odj ? bf_hi(ow) : bf_lo(ow);
                const char* ap = reinterpret_cast<const char*>(sc->A) + (loff >> 12 << 10) + ((loff & 16) >> 1);
                uint32_t on = seq != 1 && !(pst & 32);
                asm volatile("" : "+f"(cnt), "+f"(wt), "+l"(ap), "+r"(on));
                const float tot = e + e2;
                asm volatile("{\n.reg .pred p, q;\n.reg .f32 v;\nmul.f32 v, %1, %2;\nsetp.ne.u32 q, %5, %6;\nsetp.ne.and.u32 p, %4, 0, q;\n"
                             "@p red.relaxed.gpu.global.add.v2.f32 [%0], {v, %3};\n}"
                             ::"l"(ap), "f"(tot), "f"(wt), "f"(cnt), "r"(on), "r"(fl), "r"(seq) : "memory");
                sched_fence(sink);
                stsf(lst, tot * (1.f / CH));
            };
            if (info & 1) {
                hand_over(flag);
                if (info == 1 && flag != seq) goto publish;
            }
            if (flag != seq && !(info & 3)) continue;
            if (flag == seq) {
                const int tz = tid + lds32(SM_EP + 4), w = tz >> 5, g = tz >> 2 & 7, j = tz & 3;
                float x0 = fmaxf(fmaxf(rs[0] * y[0][0], rs[1] * y[0][1]), fmaxf(rs[2] * y[1][0], rs[3] * y[1][1]));
                float x1 = fmaxf(fmaxf(rs[0] * y[0][2], rs[1] * y[0][3]), fmaxf(rs[2] * y[1][2], rs[3] * y[1][3]));
                x0 = fmaxf(x0, __shfl_xor_sync(0xffffffffu, x0, 1)); x0 = fmaxf(x0, __shfl_xor_sync(0xffffffffu, x0, 2));
                x1 = fmaxf(x1, __shfl_xor_sync(0xffffffffu, x1, 1)); x1 = fmaxf(x1, __shfl_xor_sync(0xffffffffu, x1, 2));
                stsf(SM_MX + (w * 16 + g + (j & 1) * 8) * 4, (j & 1) ? x1 : x0);
                bar_sync(2, 128);
                float n0 = m0, n1 = m1;
#pragma unroll
                for (int u = 0; u < 4; ++u) { n0 = fmaxf(n0, ldsf(SM_MX + (u * 16 + g) * 4)); n1 = fmaxf(n1, ldsf(SM_MX + (u * 16 + g + 8) * 4)); }
                n0 = ceilf(n0); n1 = ceilf(n1);
                n0 = __uint_as_float((__float_as_uint(n0) + (n0 > 0.f ? __float_as_uint(n0) & 1u : 0u)) & ~1u);
                const float a0 = ex2(m0 - n0), a1 = ex2(m1 - n1);
                m0 = n0; m1 = n1;
                stsf(SM_AL + j * 32 + g * 4, j == 0 ? a0 : j == 1 ? a1 : j == 2 ? n0 : n1);
                bar_arrive(3, 256);
                softmax_p(pbuf ^ 2048);
                bar_sync(1, 256);
                l0 = fmaf(k0, a0, (p[0][0] + p[0][1]) + (p[1][0] + p[1][1]));
                l1 = fmaf(k1, a1, (p[0][2] + p[0][3]) + (p[1][2] + p[1][3]));
                if (info & 1) hand_over(0);
            }
            if (info & 2) {
                s += 3; st += 3 * STAGE_BYTES;
                if (s >= STAGES) { s -= STAGES; st -= STAGES * STAGE_BYTES; ph ^= 1; }
            }
            if (!(info & 1)) continue;
        publish:
            asm volatile("{\n.reg .pred p;\nsetp.ne.u32 p, %0, 0;\n@p bar.arrive 2, 128;\n@p exit;\n}" ::"r"((uint32_t)(seq != 1 && w != 0)) : "memory");
            const uint32_t epoch = lds32(SM_EP);
            uint32_t lsa = lst & ~140u;
            asm volatile("" : "+r"(lsa));
            bar_sync(2, 128);
            {
                uint32_t la[4], lb[4];
                lds128(lsa, la); lds128(lsa + 128, lb);
                const float sa = sum4(la), sb = sum4(lb);
                const uint32_t mt = __float_as_uint(m0) | ((epoch ^ (seq == 1)) & 1u);
                const float ha = __uint_as_float(__float_as_uint(sa) & 0xffff0000u), hb = __uint_as_float(__float_as_uint(sb) & 0xffff0000u);
                st_v4(reinterpret_cast<uint4*>(reinterpret_cast<char*>(sc->L) + loff), pack2(ha, sa - ha), pack2(hb, sb - hb), mt, __float_as_uint(m1));
            }
            if (seq != 1) return;
            sink_if(SM_EP + 8, sink, lds32(SM_EP + 4));
            m0 = m1 = -INFINITY; l0 = l1 = 0.f;
            const int tz = tid + lds32(SM_EP + 4), w = tz >> 5, lane = tz & 31;
            uint4 v[3];
            unsigned it = 0;
            while (true) {
                if (it < 2 && src >= NSERV) mbar_wait(BAR_FULL + 8 * (QK_AFTER + it), 0);
#pragma unroll
                for (int k = 0; k < 3; ++k) v[k] = ld_relaxed4(&sc->qk[(3 * w + k) * 32 + lane]);
                const uint32_t bad = (v[0].x ^ epoch) | (v[1].x ^ epoch) | (v[2].x ^ epoch);
                if (__all_sync(0xffffffffu, (bad & 1u) == 0)) break;
                spin_guard(++it);
            }
            bar_sync(6, 256);
#pragma unroll
            for (int k = 0; k < 3; ++k) stsm4(SM_XA + (3 * w + k) * 512 + lane * 16, v[k].x, v[k].y, v[k].z, v[k].w);
            bar_sync(2, 128);
#pragma unroll
            for (int k = 0; k < 12; ++k) ldsm4(SM_XA + k * 512 + lane * 16, qk[k]);
            asm volatile("fence.proxy.async.shared::cta;" ::: "memory");
            bar_sync(2, 128);
            mbar_arrive_if(BAR_EMPTY + 8 * (STAGES - 1), tz == 0);
            first = tz == 0;
            float r[4] = {0.f, 0.f, 0.f, 0.f}, r2[4] = {0.f, 0.f, 0.f, 0.f};
#pragma unroll
            for (int k = 0; k < 12; k += 2) {
                mma16816(r, qk[k][0], qk[k][1], qk[k][2], qk[k][3], 0x3F803F80u, 0x3F803F80u);
                mma16816(r2, qk[k + 1][0], qk[k + 1][1], qk[k + 1][2], qk[k + 1][3], 0x3F803F80u, 0x3F803F80u);
            }
            R0 = (r[0] + r2[0]) * (1.f / CH); R1 = (r[2] + r2[2]) * (1.f / CH);
        }
    } else if (warp < 8) {
        asm volatile("setmaxnreg.inc.sync.aligned.u32 256;");
        const uint32_t cb = opaque(cb0, lane);
        pad<4>();
        const int h = __shfl_sync(0xffffffffu, warp - 4, 0);
        uint32_t oa[3], ob[3];
#pragma unroll
        for (int b = 0; b < 3; ++b) {
            int cc = 6 * h + 2 * b + (m4 >> 1);
            int r = 3 * r8 + (cc >> 3);
            oa[b] = opaque(SB + (m4 & 1) * 12288 + r * 128 + (((cc & 7) ^ (r & 7)) << 4), lane);
            cc = 6 * h + 2 * b + (m4 & 1);
            r = 3 * (4 * (m4 >> 1) + (r8 >> 1)) + (cc >> 3);
            ob[b] = opaque(SB + 24576 + r * 128 + (((cc & 7) ^ (r & 7)) << 4), lane);
        }
        const uint32_t l16 = opaque(lane * 16, lane);
        const uint32_t vdst = opaque(mapa(SM_A + (bid & (CL - 1)) * 832 + h * 192 + ((j ^ (h >> 1 | (bid & 1) << 1)) << 4), g), lane), vbar = opaque(mapa(BAR_V, g), lane);
        uint32_t axb = SM_XA;
        float acc[6][4];
#pragma unroll
        for (int t = 0; t < 6; ++t) acc[t][0] = acc[t][1] = acc[t][2] = acc[t][3] = 0.f;
        int s = STAGES - 1; uint32_t ph = 1, pbuf = 0;
        uint32_t wf[12][3][4];
#pragma unroll
        for (int i = 0; i < 12; ++i)
#pragma unroll
            for (int c = 0; c < 4; ++c) wf[i][0][c] = wf[i][1][c] = wf[i][2][c] = 0u;
        uint32_t seq = 0, info = 0, sink = 0;
        mbar_wait(BAR_EP, 0);
        uint32_t par = ~lds32(SM_EP) & 1u;
        st_v4_if(&sc->M[(g * 128 + src) * 2 + (j & 1)], 0u, 0u, par, 0u, ((j & 2) | h) == 0);
#pragma unroll 1
        while (true) {
            if (info & 8) {
                const uint32_t lz = l16 + lds32(SM_EP + 4);
                const uint32_t pub0 = lds32(SM_AL + 64 + (lz >> 6 << 2)), pub1 = lds32(SM_AL + 96 + (lz >> 6 << 2));
                if (h == 0) stsf2(SM_OW + 32 + (lz >> 6 << 3), __uint_as_float(pub0), __uint_as_float(pub1));
                st_v4_if(&sc->M[((lz >> 6) * 128 + src) * 2 + (lz >> 4 & 1)], 0u, 0u, pub0 | par, pub1, ((lz & 32) | h) == 0);
            }
            if (info & 2) {
                const uint32_t lz = l16 + lds32(SM_EP + 4);
                asm volatile("barrier.cluster.wait.aligned;" ::: "memory");
#pragma unroll
                for (int c = 0; c < 3; ++c) {
                    mbar_wait(BAR_FULL + 8 * s, ph);
#pragma unroll
                    for (int i = 0; i < 12; ++i) ldsm4(SB + s * STAGE_BYTES + (h * 12 + i) * 512 + lz, wf[4 * c + i / 3][i % 3]);
                    bar_sync(4, 128);
                    mbar_arrive_if(BAR_EMPTY + 8 * s, (lz | h) == 0);
                    if (++s == STAGES) { s = 0; ph ^= 1; }
                }
            }
            if (info & 4) {
                float u0 = 0.f, u1 = 0.f;
#pragma unroll
                for (int t = 0; t < 6; ++t) { u0 += acc[t][0] + acc[t][1]; u1 += acc[t][2] + acc[t][3]; }
                const uint32_t lz = l16 + lds32(SM_EP + 4);
                const bool j1 = lz & 16;
                const float e = (j1 ? u1 : u0) + __shfl_xor_sync(0xffffffffu, j1 ? u0 : u1, 1);
                stsf(SM_UL + (lz & 16) * 8 + (lz >> 6 << 4) + h * 4, (e + __shfl_xor_sync(0xffffffffu, e, 2)) * (1.f / CH));
                bar_sync(4, 128);
                uint32_t ua[4], ub[4];
                lds128(SM_UL + (lz >> 6 << 4), ua); lds128(SM_UL + 128 + (lz >> 6 << 4), ub);
                u0 = sum4(ua); u1 = sum4(ub);
#pragma unroll
                for (int t = 0; t < 6; ++t) { acc[t][0] -= u0; acc[t][1] -= u0; acc[t][2] -= u1; acc[t][3] -= u1; }
            }
            auto project = [&]() {
                uint32_t af[12][4], ax[4];
#pragma unroll
                for (int i = 0; i < 4; ++i) ax[i] = axb + ((h + i) & 3) * 1536;
                const uint32_t real = seq != 1;
#pragma unroll
                for (int ks = 0; ks < 3; ++ks) {
                    af[ks][0] = pack2(acc[2 * ks][0], acc[2 * ks][1]); af[ks][1] = pack2(acc[2 * ks][2], acc[2 * ks][3]);
                    af[ks][2] = pack2(acc[2 * ks + 1][0], acc[2 * ks + 1][1]); af[ks][3] = pack2(acc[2 * ks + 1][2], acc[2 * ks + 1][3]);
                    stsm4(ax[0] + ks * 512 + l16, af[ks][0], af[ks][1], af[ks][2], af[ks][3]);
                }
                float o[4][2][4];
                constexpr int ord[36] = {0,1,2,0,1,2,0,1,2, 0,1,0,2,0,1,0,1,0,2,0,1,0,1,0,1,0, 1,2,1,2,1, 2,3,2,3,2};
                int nx[3] = {0, 0, 0};
                bool used3 = false;
#pragma unroll
                for (int z = 0; z < 36; ++z) {
                    const int a = ord[z], tp = a == 3 ? 2 : a, i = nx[tp]++;
                    if (i == 0 || (a == 3 && !used3)) {
#pragma unroll
                        for (int c = 0; c < 4; ++c) o[a][0][c] = o[a][1][c] = 0.f;
                    }
                    if (a == 3) used3 = true;
                    mma16816(o[a][0], af[i][0], af[i][1], af[i][2], af[i][3], wf[i][tp][0], wf[i][tp][1]);
                    mma16816(o[a][1], af[i][0], af[i][1], af[i][2], af[i][3], wf[i][tp][2], wf[i][tp][3]);
                    if (z == 0 || z == 2 || z == 30) sched_fence(sink);
                    if (z == 2) bar_sync(4, 128);
                    if (z == REL_Z) asm volatile("{\n.reg .pred p;\nsetp.ne.u32 p, %0, 0;\n@p bar.arrive 12, 256;\n}" ::"r"(real) : "memory");
#pragma unroll
                    for (int k = 0; k < 9; ++k) if (z == 2) ldsm4(ax[1 + k / 3] + (k % 3) * 512 + l16, af[3 + k]);
#pragma unroll
                    for (int e = 0; e < 3; ++e)
                        if (z == (e == 0 ? 26 : e == 1 ? 31 : 35)) {
                            if (e == 2) {
#pragma unroll
                                for (int c = 0; c < 4; ++c) { o[2][0][c] += o[3][0][c]; o[2][1][c] += o[3][1][c]; }
                            }
                            st_async_if(vdst + e * 64, pack2(o[e][0][0], o[e][0][1]), pack2(o[e][1][0], o[e][1][1]),
                                        pack2(o[e][0][2], o[e][0][3]), pack2(o[e][1][2], o[e][1][3]), vbar + 8 * e, real);
                        }
                }
            };
            if (!(info & 1)) {
                const uint32_t st = __shfl_sync(0xffffffffu, s * STAGE_BYTES, 0);
                axb = SB + st;
                const uint32_t lz = l16 + lds32(SM_EP + 4);
                const char* tp = reinterpret_cast<const char*>(sc->T) + ((lz >> 5 << 12) + (lz & 16) + src * 32);
                uint32_t ann = (lz >> 8 | h) == 0;
                asm volatile("" : "+l"(tp), "+r"(ann));
                mbar_wait(BAR_FULL + 8 * s, ph);
                asm volatile("{\n.reg .pred p;\n.reg .b32 t, u;\nld.shared.u32 %0, [%1];\nmov.u32 t, %%globaltimer_lo;\nlop3.b32 t, t, 1, %3, 0xba;\n"
                             "and.b32 u, %0, %4;\nsetp.ne.u32 p, u, 0;\n@p st.relaxed.gpu.global.v4.u32 [%2], {t,t,t,t};\n}"
                             : "=r"(info) : "r"(SM_INFO + 4 * s), "l"(tp), "r"(par), "r"(ann) : "memory");
                bar_sync(8, 256);
                uint32_t xt[4][3][4];
#pragma unroll
                for (int u = 0; u < 6; ++u) {
                    const int gp = u / 3, b = u % 3;
                    if (u == 5) asm volatile("{\n.reg .pred p;\nsetp.ne.u32 p, %0, 0;\n@p bar.arrive 11, 256;\n}" ::"r"((uint32_t)((info & 1) && seq != 0)) : "memory");
                    uint32_t f[4];
                    ldsm4t(st + ob[b] + gp * 3072, f);
                    ldsm4t(st + oa[b] + (2 * gp) * 3072, xt[2 * gp][b]);
                    ldsm4t(st + oa[b] + (2 * gp + 1) * 3072, xt[2 * gp + 1][b]);
                    if (u == 1 || u == 3) sched_fence(sink);
#pragma unroll
                    for (int c = 0; c < 4; ++c) {
                        xt[2 * gp][b][c] = badd2v(xt[2 * gp][b][c], f[c >> 1]);
                        xt[2 * gp + 1][b][c] = badd2v(xt[2 * gp + 1][b][c], f[2 + (c >> 1)]);
                    }
                }
                ++seq;
                const uint32_t pb = pbuf;
                pbuf ^= 2048;
                if (++s == STAGES) { s = 0; ph ^= 1; }
                auto accumulate = [&]() {
                    uint32_t pa[4][4], fa = SM_FLAG + (pb >> 9);
#pragma unroll 1
                    while (true) {
                        if (fa == SM_EP + 4) {
                            bar_sync(3, 256);
                            const uint32_t gz = (l16 + lds32(SM_EP + 4)) >> 6 << 2;
                            const float a0 = ldsf(SM_AL + gz), a1 = ldsf(SM_AL + 32 + gz);
#pragma unroll
                            for (int t = 0; t < 6; ++t) { acc[t][0] *= a0; acc[t][1] *= a0; acc[t][2] *= a1; acc[t][3] *= a1; }
                        }
                        bar_sync(1, 256);
                        uint32_t flag;
                        asm volatile("ld.shared.u32 %4, [%6];\nldmatrix.sync.aligned.m8n8.x4.shared.b16 {%0,%1,%2,%3}, [%5];"
                                     : "=r"(pa[0][0]), "=r"(pa[0][1]), "=r"(pa[0][2]), "=r"(pa[0][3]), "=r"(flag) : "r"(SM_P + l16 + pb), "r"(fa) : "memory");
                        fa = SM_EP + 4;
                        if (flag != seq) break;
                    }
#pragma unroll
                    for (int gq = 1; gq < 4; ++gq) ldsm4(SM_P + l16 + pb + gq * 512, pa[gq]);
#pragma unroll
                    for (int gq = 0; gq < 4; ++gq)
#pragma unroll
                        for (int b = 0; b < 3; ++b) {
                            mma16816(acc[2 * b], pa[gq][0], pa[gq][1], pa[gq][2], pa[gq][3], xt[gq][b][0], xt[gq][b][1]);
                            mma16816(acc[2 * b + 1], pa[gq][0], pa[gq][1], pa[gq][2], pa[gq][3], xt[gq][b][2], xt[gq][b][3]);
                        }
                };
                if (info != 1) { accumulate(); continue; }
                accumulate();
                project();
            } else {
                project();
            }
            if (seq != 1) break;
            sink_if(SM_EP + 8, sink, lds32(SM_EP + 4));
            asm volatile("fence.proxy.async.shared::cta;" ::: "memory");
            bar_arrive(6, 256);
            par ^= 1u;
            info = 0;
#pragma unroll
            for (int t = 0; t < 6; ++t) acc[t][0] = acc[t][1] = acc[t][2] = acc[t][3] = 0.f;
        }
    } else {
        asm volatile("setmaxnreg.dec.sync.aligned.u32 72;");
        const uint32_t cb = opaque(cb0, lane);
        const int fw = __shfl_sync(0xffffffffu, warp - 8, 0);
        if (fw == 0) {
            if (src < NSERV) {
                el_expect_tx(BAR_FULL, STAGE_BYTES);
                el_tile(cb, 0, JOIN_N * NE + src, &tm0, &tm1);
            }
            el_expect_tx(BAR_FULL + 8, STAGE_BYTES);
            el_tile(cb, 1, src < NSERV ? JOIN_N * NE + NS + src : src - NSERV + NE, &tm0, &tm1);
            el_arrive(BAR_FULL);
        } else if (fw == 1) {
            const unsigned epoch = __shfl_sync(0xffffffffu, ticket + 1, 0);
            sts32(SM_EP, epoch);
            el_arrive(BAR_EP);
            stsf2(SM_FLAG + 8, __uint_as_float(now_ns()), __uint_as_float(clk32()));
            __nanosleep(6000);
            unsigned it = 0;
            while (!__all_sync(0xffffffffu, ld_acquire(sc->flagW + min(lane, NSERV - 1) * 8) == epoch)) { spin_guard(++it); __nanosleep(64); }
            asm volatile("fence.proxy.async;" ::: "memory");
            __syncwarp();
            el_arrive(BAR_W);
        } else if (fw == 3) {
            if (lane < CL) sts32(SM_OW + 4 * lane, ~0u);
            asm volatile("barrier.cluster.arrive.relaxed.aligned;" ::: "memory");
        }
        uint32_t sink = 0;
        int slot = 2, n = fw ? 0 : src < NSERV ? JOIN_N + 2 : 2, sp = 1, sd = 0;
        uint32_t pp = 0, pd = 0;
#pragma unroll 1
        for (int real = 0; ; ++real) {
        {
            const int wat = CHECKPOINT + (bid & WSTAG), pause = real ? 0 : PAUSE + (bid >> 4 & 7);
            auto wait_empty = [&](int sl) {
                const int r = (sl * 37) >> 8, st = sl - r * STAGES;
                mbar_wait_u(BAR_EMPTY + 8 * st, (r ^ (st != STAGES - 1)) & 1);
                return st;
            };
            while (n != pause && n != 0) {
                const int t = n < JOIN_N ? src - NSERV + n * NE : n < NSTATIC ? src + n * NS - JOIN_N * NSERV : NSTATIC * NS - JOIN_N * NSERV + __shfl_sync(0xffffffffu, ticket, 0);
                const bool done = t >= NTILES, winj = n == wat || (done && n < wat);
                sts32(SM_INFO + 4 * sp, done + 2 * winj + 4 * ((unsigned)(NTILES - END_X - t) < (unsigned)(2 * NS)) + 8 * (n == MX_AT || (done && n < MX_AT)));
                sts32(SM_INFO + 4 * STAGES, done ? ~0u : n);
                el_arrive(BAR_FULL + 8 * sp);
                const int wslot = slot;
                if (winj) slot += 3;
                if (!done) {
                    const int s = wait_empty(slot);
                    el_expect_tx(BAR_FULL + 8 * s, STAGE_BYTES);
                    mbar_wait_u(BAR_FULL + 8 * sd, pd);
                    if (n >= MID_FROM || t >= NTILES - END_X) {
                        const uint32_t c0 = clk32(), hold = t >= NTILES - END_X ? D_END : MID_D;
                        while (clk32() - c0 < hold && !mbar_test(BAR_FULL + 8 * sp, pp)) __nanosleep(50);
                    }
                    asm volatile("{\n.reg .pred p;\nsetp.ne.u32 p, %2, 0;\n@p atom.relaxed.gpu.global.inc.u32 %0, [%1], 0x7fffffff;\n}"
                                 : "+r"(ticket) : "l"(&sc->ctr), "r"((uint32_t)(n >= NSTATIC - 1 && lane == 0)) : "memory");
                    el_tile(cb, s, t, &tm0, &tm1);
                    sd = sp; pd = pp; sp = s; pp = ((slot * 37) >> 8) & 1;
                    ++n;
                    if (++slot >= 2 * STAGES) slot -= 2 * STAGES;
                } else {
                    n = 0;
                }
                if (winj) {
                    mbar_wait_u(BAR_W, 0);
#pragma unroll 1
                    for (int c = 0; c < 3; ++c) {
                        const int st = wait_empty(wslot + c);
                        el_expect_tx(BAR_FULL + 8 * st, 24576);
                        el_bulk(SB + st * STAGE_BYTES, sc->wvo + c * 6144, 24576, BAR_FULL + 8 * st);
                        el_arrive(BAR_FULL + 8 * st);
                    }
                }
            }
        }
        if (fw == 0) bar_arrive(7, 128);
        {
            const int ft = tid - 256 + lds32(SM_EP + 4), lane = ft & 31, g = lane >> 2, j = lane & 3;
            const int n0 = src & (CL - 1);
            const uint32_t epoch = lds32(SM_EP), par = epoch & 1u;
            unsigned it = 0;
            if (fw == 1 && real) {
                const uint4* xp = &(real > 1 ? sc->L : sc->M)[(n0 * 128 + lane) * 2];
                uint4 x[4];
                while ((uint32_t)ldsv32(SM_INFO + 4 * STAGES) < WT_AT) { __nanosleep(1000); spin_guard(++it); }
                while (true) {
#pragma unroll
                    for (int i = 0; i < 4; ++i) {
                        x[i] = make_uint4(0u, 0u, 0xff7ffffeu | par, 0xff7fffffu);
                        ld_relaxed4_if(x[i], xp + 64 * i, 32 * i + lane < NS);
                    }
                    if (!__any_sync(0xffffffffu, ((x[0].z ^ par) | (x[1].z ^ par) | (x[2].z ^ par) | (x[3].z ^ par)) & 1u)) break;
                    if (real == 1) __nanosleep(1000);
                    spin_guard(++it);
                }
#pragma unroll
                for (int i = 0; i < 4; ++i) x[i].z &= ~1u;
                const float Xa = warp_max(fmaxf(fmaxf(__uint_as_float(x[0].z), __uint_as_float(x[1].z)), fmaxf(__uint_as_float(x[2].z), __uint_as_float(x[3].z))));
                const float Xb = warp_max(fmaxf(fmaxf(__uint_as_float(x[0].w), __uint_as_float(x[1].w)), fmaxf(__uint_as_float(x[2].w), __uint_as_float(x[3].w))));
                uint32_t own = 0;
#pragma unroll
                for (int i = 0; i < 4; ++i) {
                    const uint32_t w2 = pack2(ex2(__uint_as_float(x[i].z) - Xa), ex2(__uint_as_float(x[i].w) - Xb));
                    if (i == src >> 5) own = w2;
                    sts16(SM_FW + (32 * i + lane) * 2, w2); sts16(SM_FW + 272 + (32 * i + lane) * 2, w2 >> 16);
                }
                __syncwarp();
                el_arrive(BAR_WT);
                if (real == 1) {
                    asm volatile("barrier.cluster.wait.aligned;" ::: "memory");
                    asm volatile("{\n.reg .pred p;\nsetp.ne.u32 p, %2, 0;\n@p st.relaxed.cluster.shared::cluster.u32 [%0], %1;\n}"
                                 ::"r"(mapa(SM_OW + n0 * 4, lane & (CL - 1))), "r"(own), "r"((uint32_t)(((lane ^ src) >> 3 & 3) == 0)) : "memory");
                }
            }
            const uint32_t valid = real && 32 * fw + lane < NS;
            const uint4* lp = scl + (n0 * 128 + min(32 * fw + lane, NS - 1)) * 2;
            sched_fence(sink);
            if (fw) bar_sync(7, 128);
            else mbar_wait_u(real ? BAR_WT : BAR_EP, real ? ~real & 1 : 0);
            uint32_t aq[4], meta = (g < 4 ? 0x4444u : 0xEEEEu) | 0x44440000u;
            {
                const uint32_t wp = SM_FW + (g & 1) * 272 + ((src & ~(CL - 1)) + (j & ~1)) * 2;
                uint32_t w = __byte_perm(lds32(wp), lds32(wp + 8), j & 1 ? 0x7632 : 0x5410);
                asm volatile("mul.rn.bf16x2 %0, %0, %1;" : "+r"(w) : "r"(0x43404340u));
                aq[0] = g & 2 ? w << 16 : w & 0xffffu; aq[2] = g & 2 ? w & 0xffff0000u : w >> 16;
                aq[1] = aq[3] = lds32(SM_EP + 4);
            }
            const float2 ts = ldsf2(SM_FLAG + 8);
            uint32_t t0 = __float_as_uint(ts.x);
            const float nspc = fminf(__fdividef((float)(now_ns() - t0), (float)(clk32() - __float_as_uint(ts.y))), 2.f);
            uint32_t llag = t0 + MEMNS + f2uv(nspc * LLAG);
            uint32_t vsrc = SM_A + (lane >> 2) * 832 + ((lane & 3) * 3 + fw) * 64 + (((lane >> 1 & 1) | (lane >> 1 & 2)) << 4);
            uint32_t vb = real && fw < 3 ? BAR_V + 8 * fw : BAR_EP;
            uint32_t id = 0x3210 + lds32(SM_EP + 4), chk = valid ? ~0u : 0u, on = real == 1;
            uint32_t wr = real && fw < 3 && (g & 1) == (j >> 1) ? 0 : 3, epw = real;
            __nv_bfloat16* op = out + (n0 + (j >> 1) * 8) * CH + 48 * (g >> 1) + 16 * fw + 8 * (j & 1);
            const float2* ap = reinterpret_cast<const float2*>(&sc->A[n0 * 64]) + (j >> 1);
            float want = real ? (float)(4 * NS) : 0.f;
            asm volatile("" : "+l"(lp), "+l"(op), "+l"(ap), "+r"(vsrc), "+r"(vb), "+r"(meta), "+r"(aq[0]), "+r"(aq[2]), "+r"(chk), "+r"(wr), "+r"(id), "+r"(on), "+r"(epw), "+f"(want), "+r"(llag), "+r"(t0));
            sched_fence(sink);
            if (real == 1) bar_sync(11, 256);
            {
                sts32(SM_FIN + fw * 4, __reduce_max_sync(0xffffffffu, (collect(lp + 8 * 128 * 2, par, on) - t0) & (on ? chk : 0u)));
                bar_sync(13, 128);
                uint32_t t4[4];
                lds128(SM_FIN, t4);
                llag += max(max(t4[0], t4[1]), max(t4[2], t4[3]));
                asm volatile("{\n.reg .pred p;\nsetp.eq.u32 p, %2, 0;\n@p st.global.v2.u32 [%0], {%1, %2};\n}" ::"l"(&sc->epoch), "r"(epoch), "r"(src | fw | lane | !on) : "memory");
            }
            if (real == 1) bar_sync(12, 256);
            float2 la = make_float2(1.f, 0.f);
            load_at(la, on, llag, ap, id);
            if (fw == 3 && on) {
                while (__any_sync(0xffffffffu, ldsv32(SM_OW + (lane & 7) * 4) == ~0u)) spin_guard(++it);
            }
            float r[8];
            {
                mbar_wait_u(vb, 0);
                uint32_t bv[4][4];
#pragma unroll
                for (int u = 0; u < 4; ++u) ldsm4t(vsrc ^ (u << 4), bv[u]);
#pragma unroll
                for (int u = 0; u < 4; ++u) {
                    float c[4];
                    mma_sp(c, aq, bv[u], meta);
                    r[2 * u] = c[0]; r[2 * u + 1] = c[1];
                }
            }
            sched_fence(sink);
            asm volatile("{\n.reg .pred p, q;\n.reg .f32 i, t<8>;\n.reg .b32 a, b, c, d;\n"
                         "rcp.approx.ftz.f32 i, %0;\nsetp.eq.f32 q, %1, %2;\nsetp.lt.and.u32 p, %11, 3, q;\n"
                         "mul.f32 t0, %3, i;\nmul.f32 t1, %4, i;\nmul.f32 t2, %5, i;\nmul.f32 t3, %6, i;\n"
                         "mul.f32 t4, %7, i;\nmul.f32 t5, %8, i;\nmul.f32 t6, %9, i;\nmul.f32 t7, %10, i;\n"
                         "cvt.rn.bf16x2.f32 a, t1, t0;\ncvt.rn.bf16x2.f32 b, t3, t2;\ncvt.rn.bf16x2.f32 c, t5, t4;\ncvt.rn.bf16x2.f32 d, t7, t6;\n"
                         "@p red.global.add.noftz.v4.bf16x2 [%12], {a, b, c, d};\n"
                         "setp.ne.and.u32 p, %13, 0, q;\n@p exit;\n"
                         "}"
                         ::"f"(la.x), "f"(la.y), "f"(want), "f"(r[0]), "f"(r[1]), "f"(r[2]), "f"(r[3]), "f"(r[4]), "f"(r[5]), "f"(r[6]), "f"(r[7]),
                           "r"(wr), "l"(op), "r"(epw) : "memory");
            uint32_t redo = 0;
            if (la.y != want) {
                float L;
                if (real == 1) {
                    while ((f2uv(la.y) & 2047u) != (unsigned)(4 * NS)) {
                        asm volatile("ld.relaxed.gpu.global.v2.f32 {%0,%1}, [%2];" : "=f"(la.x), "=f"(la.y) : "l"(ap) : "memory");
                        spin_guard(++it);
                    }
                    redo = la.y != want;
                    L = la.x;
                } else {
                    const int lz = lane + lds32(SM_EP + 4), gz = lz >> 2, jz = lz & 3;
                    uint32_t wa[4], b[4];
                    const float2 x = ldsf2(SM_FW + (gz & 1) * 272 + fw * 64 + jz * 8), y = ldsf2(SM_FW + (gz & 1) * 272 + fw * 64 + 32 + jz * 8);
                    wa[0] = __float_as_uint(x.x); wa[1] = __float_as_uint(x.y); wa[2] = __float_as_uint(y.x); wa[3] = __float_as_uint(y.y);
                    const uint32_t ldst = SB + (fw * 32 + lz) * 16;
                    uint4 l = make_uint4(0u, 0u, 0u, 0u);
                    ld_relaxed4_if(l, lp, chk);
                    asm volatile("st.shared.v4.u32 [%0], {%1,%2,%3,%4};" ::"r"(ldst), "r"(l.x), "r"(l.y), "r"(l.z), "r"(l.w) : "memory");
                    __syncwarp();
                    ldsm4t(ldst, b);
                    float c[4];
                    mma_sp(c, wa, b);
                    asm volatile("{\n.reg .pred p;\nsetp.ne.u32 p, %2, 0;\n@p st.shared.f32 [%0], %1;\n}"
                                 ::"r"(SM_FIN + 32 + (lz == 5) * 16 + fw * 4), "f"((c[0] + c[2]) + (c[1] + c[3])), "r"((uint32_t)(lz == 0 || lz == 5)) : "memory");
                    bar_sync(13, 128);
                    uint32_t d[4];
                    lds128(SM_FIN + 32 + (jz >> 1) * 16, d);
                    L = sum4(d) * (float)CH;
                }
                float inv;
                asm volatile("rcp.approx.ftz.f32 %0, %1;" : "=f"(inv) : "f"(L));
                red_if(op, pack2(r[0] * inv, r[1] * inv), pack2(r[2] * inv, r[3] * inv), pack2(r[4] * inv, r[5] * inv), pack2(r[6] * inv, r[7] * inv), !redo && wr < 3);
            }
            if (real && !redo) return;
            sink_if(SM_EP + 8, sink, lds32(SM_EP + 4));
            bar_sync(9, 128);
            spin_guard(real);
        }
        }
    }
}

typedef CUresult (*EncodeFn)(CUtensorMap*, CUtensorMapDataType, cuuint32_t, void*, const cuuint64_t*, const cuuint64_t*,
                             const cuuint32_t*, const cuuint32_t*, CUtensorMapInterleave, CUtensorMapSwizzle,
                             CUtensorMapL2promotion, CUtensorMapFloatOOBfill);

}

extern "C" void kernel_launch(void* const* d_in, const int* in_sizes, int n_in, void* d_out, int out_size) {
    (void)in_sizes; (void)n_in; (void)out_size;
    static EncodeFn enc = nullptr;
    static int grid = 0;
    static Scratch* scratch = nullptr;
    if (!enc) {
        cudaDriverEntryPointQueryResult qr;
        cudaGetDriverEntryPoint("cuTensorMapEncodeTiled", (void**)&enc, cudaEnableDefault, &qr);
        cudaGetSymbolAddress((void**)&scratch, g_s);
        int dev = 0, sms = 0;
        cudaGetDevice(&dev);
        cudaDeviceGetAttribute(&sms, cudaDevAttrMultiProcessorCount, dev);
        (void)sms;
        cudaFuncSetAttribute(fused_kernel, cudaFuncAttributeMaxDynamicSharedMemorySize, SM_TOTAL);
        cudaLaunchConfig_t cfg = {};
        cfg.gridDim = dim3(MAXS); cfg.blockDim = dim3(384); cfg.dynamicSmemBytes = SM_TOTAL;
        cudaLaunchAttribute at[1]; at[0].id = cudaLaunchAttributeClusterDimension; at[0].val.clusterDim.x = CL; at[0].val.clusterDim.y = 1; at[0].val.clusterDim.z = 1;
        cfg.attrs = at; cfg.numAttrs = 1;
        int ncl = 0;
        cudaOccupancyMaxActiveClusters(&ncl, fused_kernel, &cfg);
        grid = (ncl < MAXS / CL ? ncl : MAXS / CL) * CL;
    }
    CUtensorMap tm0, tm1, tmq, tmk, tmv, tmo;
    {
        cuuint64_t gd[3] = {64, 1536, 512}; cuuint64_t gs[2] = {128, 196608};
        cuuint32_t bd[3] = {64, 96, 2}; cuuint32_t es[3] = {1, 1, 1};
        enc(&tm0, CU_TENSOR_MAP_DATA_TYPE_BFLOAT16, 3, d_in[1], gd, gs, bd, es, CU_TENSOR_MAP_INTERLEAVE_NONE,
            CU_TENSOR_MAP_SWIZZLE_128B, CU_TENSOR_MAP_L2_PROMOTION_L2_64B, CU_TENSOR_MAP_FLOAT_OOB_FILL_NONE);
    }
    auto map2d = [&](CUtensorMap* tm, void* p, cuuint64_t cols, cuuint64_t rows, cuuint32_t bc, cuuint32_t br, CUtensorMapSwizzle sw) {
        cuuint64_t gd[2] = {cols, rows}; cuuint64_t gs[1] = {cols * 2};
        cuuint32_t bd[2] = {bc, br}; cuuint32_t es[2] = {1, 1};
        enc(tm, CU_TENSOR_MAP_DATA_TYPE_BFLOAT16, 2, p, gd, gs, bd, es, CU_TENSOR_MAP_INTERLEAVE_NONE,
            sw, CU_TENSOR_MAP_L2_PROMOTION_L2_64B, CU_TENSOR_MAP_FLOAT_OOB_FILL_NONE);
    };
    map2d(&tm1, d_in[2], 64, 196608, 64, 48, CU_TENSOR_MAP_SWIZZLE_128B);
    map2d(&tmq, d_in[3], 64, 576, 64, 192, CU_TENSOR_MAP_SWIZZLE_128B);
    map2d(&tmk, d_in[4], 64, 576, 64, 48, CU_TENSOR_MAP_SWIZZLE_128B);
    map2d(&tmv, d_in[5], 64, 576, 64, 192, CU_TENSOR_MAP_SWIZZLE_128B);
    map2d(&tmo, d_in[6], 192, 192, 16, 192, CU_TENSOR_MAP_SWIZZLE_NONE);
    fused_kernel<<<grid, 384, SM_TOTAL>>>((uint64_t)scratch | (grid - 1), (const __nv_bfloat16*)d_in[0], (const char*)d_in[1], (const char*)d_in[2],
                                          (const char*)d_in[3], (const char*)d_in[4], tm0, tm1, tmq, tmk, tmv, tmo, (__nv_bfloat16*)d_out, scratch->L);
}
```
